```python
import torch

def _softmax(x, axis=-1):
    return torch.softmax(x, dim=axis)
def _gelu(x):
    return torch.nn.functional.gelu(x, approximate="tanh")
def _silu(x):
    return torch.nn.functional.silu(x)
def _sigmoid(x):
    return torch.sigmoid(x)
def _layernorm(x, axis=-1, eps=1e-5):
    m = x.mean(dim=axis, keepdim=True)
    v = x.var(dim=axis, keepdim=True, unbiased=False)
    return (x - m) / torch.sqrt(v + eps)
def _scatter_add(tgt, idx, src, axis=0):
    return tgt.clone().index_add_(axis, idx, src)
def _segment_sum(src, seg, n):
    out = torch.zeros((n,) + src.shape[1:], dtype=src.dtype)
    return out.index_add_(0, seg, src)
def _pad(x, pw):
    flat = tuple(v for pair in reversed(pw) for v in pair)
    return torch.nn.functional.pad(x, flat)

kernel_name = 'gated_mix__linear_attn_block__moe_arch_mod__prompt'

def setup_inputs():

    _w = (lambda a: (lambda t: t.to(torch.bfloat16) if t.is_floating_point() else t)(torch.as_tensor(a)))
    def _A_setup():
        B, S, D = 1, 2048, 1024
        return {
            "x": _w((lambda *s: torch.randn(*s, dtype=torch.bfloat16) * 0.05)(B, S, D)),
            "wqkv": _w((lambda *s: torch.randn(*s, dtype=torch.bfloat16) * 0.8)(D, 3 * D)),
            "wo": _w((lambda *s: torch.randn(*s, dtype=torch.bfloat16) * 0.1)(D, D)),
        }
    _A_in = _A_setup()

    def _B_setup():
        B, S, D, F, C = 1, 2048, 1024, 3584, 1
        return {
            "x": _w((lambda *s: torch.randn(*s, dtype=torch.bfloat16) * 0.05)(B, S, D)),
            "w_r": _w((lambda *s: torch.randn(*s, dtype=torch.bfloat16) * 1.6)(D)),
            "w_gate": _w((lambda *s: torch.randn(*s, dtype=torch.bfloat16) * 0.1)(D, F)),
            "w_up": _w((lambda *s: torch.randn(*s, dtype=torch.bfloat16) * 0.1)(D, F)),
            "w_down": _w((lambda *s: torch.randn(*s, dtype=torch.bfloat16) * 0.1)(F, D)),
        }
    _B_in = _B_setup()

    return {
        "A_x": _A_in["x"],
        "A_wqkv": _A_in["wqkv"],
        "A_wo": _A_in["wo"],
        "B_x": _B_in["x"],
        "B_w_r": _B_in["w_r"],
        "B_w_gate": _B_in["w_gate"],
        "B_w_up": _B_in["w_up"],
        "B_w_down": _B_in["w_down"],
        "gate_w": _w((lambda *s: torch.randn(*s, dtype=torch.bfloat16) * 0.05)(1024) * 16.0),
    }

def reference(A_x, A_wqkv, A_wo, B_x, B_w_r, B_w_gate, B_w_up, B_w_down, gate_w):
    def _A_ref(x, wqkv, wo):
        B, S, D = x.shape
        H = 32; Dh = D // H
        qkv = (lambda x, *d: x.permute(*d))((x @ wqkv).reshape(B, S, 3, H, Dh), 2, 0, 3, 1, 4)
        q, k, v = qkv[0], qkv[1], qkv[2]
        phi = lambda t: torch.where(t > 0, t + 1, torch.exp(t)) + 1e-6
        pq, pk = phi(q), phi(k)
        kv = torch.einsum("bhsd,bhse->bhde", pk, v)
        z = torch.einsum("bhsd->bhd", pk)
        num = torch.einsum("bhqd,bhde->bhqe", pq, kv)
        den = torch.einsum("bhqd,bhd->bhq", pq, z)[..., None] + 1e-6
        o = num / den
        return (lambda x, *d: x.permute(*d))(o, 0, 2, 1, 3).reshape(B, S, D) @ wo

    def _B_ref(x, w_r, w_gate, w_up, w_down):
        B, S, D = x.shape
        C = 1
        r = x @ w_r
        idx = torch.argsort(-r, axis=-1)[:, :C]
        idx_e = (lambda x, n, axis: torch.repeat_interleave(x, n, dim=axis))(idx.reshape(B, C, 1), D, axis=2)
        x_sel = (lambda x, i, axis: torch.take_along_dim(x, i, dim=axis))(x, idx_e, axis=1)
        g = _silu(x_sel @ w_gate)
        u = x_sel @ w_up
        y = (g * u) @ w_down
        r_sel = _sigmoid((lambda x, i, axis: torch.take_along_dim(x, i, dim=axis))(r, idx, axis=1))
        y = y * r_sel.reshape(B, C, 1)
        b_off = (torch.arange(B) * S).reshape(B, 1)
        flat_idx = (idx + b_off).reshape(B * C)
        zero = (x * 0.0).reshape(B * S, D)
        upd = _scatter_add(zero, flat_idx, y.reshape(B * C, D), axis=0)
        return x + upd.reshape(B, S, D)

    x = A_x
    g = _sigmoid((x * gate_w).sum(-1, keepdims=True))
    a = _A_ref(x, A_wqkv, A_wo)
    b = _B_ref(x, B_w_r, B_w_gate, B_w_up, B_w_down)
    return g * a + (1 - g) * b
```

```cpp
#include <cuda_runtime.h>
#include <cuda.h>
#include <cuda_bf16.h>
#include <stdint.h>
#include <stddef.h>

namespace {

constexpr int S_ = 2048, D_ = 1024, F_ = 3584;
constexpr int NCTA = 128, NGRID = 132, NTHREADS = 512;
constexpr int MOD_CTAS = F_ / 32;

#define PC 2
#define PRE 2
#define ST1 700
#define RT_G0 2
#define RT_ROT 2
#define RT_SLEEP 500
#define PF_MOD 6
#define MOD_START 9
#define MM 4
#define PA 4
#define RED_SLEEP 32
#define RETRY 1
#define KV_SLEEP_A 128
#define KV_SLEEP 50
#define OWN 5
#define TL 3
#define MAP 1
#define NOMOD 5
#define FIXR 2
#define PH 0
#define KVE 8
#define MX 1
#define FENCES 0
#define FSL 128
#define AFLAG 1
#define AW 1
#define SK 2
#define AREL 0
#define M0 1
#define M1 1
#define OWNH 0
#define PAIRED 1
#define BYSM 1

constexpr uint32_t A_BYTES = 16384, BQ_BYTES = 24576, BO_BYTES = 16384, STAGE_BYTES = A_BYTES + BQ_BYTES, O_BYTES = A_BYTES + BO_BYTES;
constexpr int MOD_BUFS = 3, MOD_BUFS0 = MOD_BUFS + MX;
static_assert(MOD_START + MOD_BUFS0 <= 16, "first FFN round is requested during wave A");
constexpr uint32_t OFF_RING = 0;
constexpr uint32_t OFF_MOD = 4 * STAGE_BYTES;
constexpr uint32_t OFF_PK = OFF_MOD + MOD_BUFS * 8192;
constexpr uint32_t OFF_V = OFF_PK + 16384;
constexpr uint32_t OFF_ONES = OFF_V + 16384;
constexpr uint32_t OFF_KVB = OFF_ONES + 2048;
constexpr uint32_t OFF_XSEL = OFF_KVB + 5120;
constexpr uint32_t OFF_G = OFF_XSEL + 2048;
constexpr uint32_t OFF_PART = OFF_G + 512;
constexpr uint32_t OFF_MISC = OFF_PART + 576;
constexpr uint32_t OFF_BAR = OFF_MISC + 32;
constexpr uint32_t BAR_FULL = OFF_BAR, BAR_EMPTY = OFF_BAR + 40, BAR_RTD = OFF_BAR + 80, BAR_Y = OFF_BAR + 88, BAR_DONE = OFF_BAR + 96,
                   BAR_X = OFF_BAR + 104, BAR_OA = OFF_BAR + 112, BAR_OWN = OFF_BAR + 120, BAR_OST = OFF_BAR + 128, BAR_PA = OFF_BAR + 136,
                   BAR_W31 = OFF_BAR + 144, BAR_MFULL = OFF_BAR + 152, BAR_MEMPTY = BAR_MFULL + MOD_BUFS0 * 8,
                   BAR_IDX = BAR_MEMPTY + MOD_BUFS * 8,
                   BAR_OWN0 = BAR_IDX + 8;
constexpr uint32_t SMEM_BYTES = OFF_BAR + 384;
static_assert(SMEM_BYTES <= 232448, "smem");

constexpr uint32_t BAR_LAND = OFF_BAR + 256, BAR_FIX = BAR_LAND + 64;
constexpr uint32_t BAR_RT = BAR_FIX;
static_assert(TL == 3 && PRE == 2 && BAR_OWN0 - OFF_BAR < 256, "warp w initialises barriers 2w and 2w + 1");
constexpr __host__ __device__ uint64_t bar_counts(int first) {
  uint64_t r = 0;
  for (uint32_t i = 0; i < 16; i++) {
    const uint32_t b = OFF_BAR + (first + i) * 8;
    const uint64_t c = b < BAR_EMPTY ? 2 : b == BAR_IDX ? 5 : b == BAR_Y || b == BAR_X || (b >= BAR_PA && b < BAR_MEMPTY) ? 1 : 4;
    r |= c << i * 4;
  }
  return r;
}

constexpr int NB_WG0 = 1, NB_ORDER_AB = 3, NB_ORDER_BO = 4, NB_STG = 5, NB_MODW = 6, NB_KEY = 7, NB_CHK = 8;

#ifndef NV
#define NV 5
#endif
constexpr int NCLR = NV * 4 + 5;
struct Scratch {
  float4 kv[2][8][NV][128];
  float y[8][D_];
  unsigned cnt[64][32];
  unsigned gslot[S_];
  unsigned rslot[8][NCTA];
  unsigned spare[128];
  unsigned block[NCTA];
  uint4 o[16][16][1024];
};
static_assert(offsetof(Scratch, gslot) == NCTA * NCLR * 64, "clear size");
__device__ __align__(1024) Scratch g_scratch;

#define PROF(cond, i) do {} while (0)
#define PROF_C(cond, i) do {} while (0)
#define PROF_P(cond, i) do {} while (0)
#define PROF_V(cond, i, v) do {} while (0)

__device__ __forceinline__ void mbar_init(uint32_t bar, int cnt) { asm volatile("mbarrier.init.shared::cta.b64 [%0], %1;" ::"r"(bar), "r"(cnt)); }
__device__ __forceinline__ void mbar_expect_tx(uint32_t bar, uint32_t bytes) { asm volatile("mbarrier.arrive.expect_tx.shared::cta.b64 _, [%0], %1;" ::"r"(bar), "r"(bytes) : "memory"); }
__device__ __forceinline__ void mbar_arrive(uint32_t bar) { asm volatile("mbarrier.arrive.shared::cta.b64 _, [%0];" ::"r"(bar) : "memory"); }
__device__ __forceinline__ uint32_t peer_addr(uint32_t a) {
  uint32_t r;
  asm volatile("{\n.reg .u32 c;\nmov.u32 c, %%cluster_ctarank;\nxor.b32 c, c, 1;\nmapa.shared::cluster.u32 %0, %1, c;\n}" : "=r"(r) : "r"(a));
  return r;
}
__device__ __forceinline__ void mbar_arrive_peer(uint32_t bar) { asm volatile("mbarrier.arrive.shared::cluster.b64 _, [%0];" ::"r"(bar) : "memory"); }
__device__ __forceinline__ uint32_t mism(uint32_t a, uint32_t b, uint32_t p) {
  uint32_t r; asm("lop3.b32 %0, %1, %2, %3, 0x7E;" : "=r"(r) : "r"(a), "r"(b), "r"(p)); return r;
}
__device__ __forceinline__ bool elect() {
  uint32_t r;
  asm volatile("{\n.reg .pred p;\nelect.sync _|p, 0xffffffff;\nselp.u32 %0, 1, 0, p;\n}" : "=r"(r));
  return r;
}
__device__ __forceinline__ uint32_t fresh_tid() { uint32_t r; asm volatile("mov.u32 %0, %%tid.x;" : "=r"(r)); return r; }
__device__ __forceinline__ void mbar_arrive_warp(uint32_t bar) {
  asm volatile("{\n.reg .pred p;\nelect.sync _|p, 0xffffffff;\n@p mbarrier.arrive.shared::cta.b64 _, [%0];\n}" ::"r"(bar) : "memory");
}
__device__ __forceinline__ void mbar_wait(uint32_t bar, uint32_t parity) {
  asm volatile("{\n.reg .pred p;\nWAIT_L:\nmbarrier.try_wait.parity.shared::cta.b64 p, [%0], %1;\n@p bra DONE_L;\nbra WAIT_L;\nDONE_L:\n}"
               ::"r"(bar), "r"(parity) : "memory");
}
__device__ __forceinline__ uint32_t mbar_test(uint32_t bar, uint32_t parity) {
  uint32_t ok;
  asm volatile("{\n.reg .pred p;\nmbarrier.test_wait.parity.shared::cta.b64 p, [%1], %2;\nselp.u32 %0, 1, 0, p;\n}" : "=r"(ok) : "r"(bar), "r"(parity) : "memory");
  return ok;
}
constexpr unsigned long long WATCHDOG_NS = 2000000000ull;
__device__ __forceinline__ unsigned long long gtime() { unsigned long long t; asm volatile("mov.u64 %0, %%globaltimer;" : "=l"(t)); return t; }
__device__ __forceinline__ uint32_t clock32() { uint32_t t; asm volatile("mov.u32 %0, %%clock;" : "=r"(t)); return t; }
__device__ __forceinline__ void mbar_wait_bounded(uint32_t bar, uint32_t parity) {
  unsigned long long t0 = 0;
  for (;;) {
    uint32_t ok;
    asm volatile("{\n.reg .pred p;\nmbarrier.try_wait.parity.shared::cta.b64 p, [%1], %2;\nselp.u32 %0, 1, 0, p;\n}" : "=r"(ok) : "r"(bar), "r"(parity) : "memory");
    if (ok) break;
    const unsigned long long t1 = gtime();
    if (t0 == 0) t0 = t1;
    if (t1 - t0 > WATCHDOG_NS) __trap();
  }
}
__device__ __forceinline__ void tma2d(uint32_t dst, const CUtensorMap* m, int c0, int c1, uint32_t bar) {
  asm volatile("cp.async.bulk.tensor.2d.shared::cluster.global.mbarrier::complete_tx::bytes [%0], [%1, {%3, %4}], [%2];"
               ::"r"(dst), "l"(m), "r"(bar), "r"(c0), "r"(c1) : "memory");
}
__device__ __forceinline__ void tma3d(uint32_t dst, const CUtensorMap* m, int c0, int c1, int c2, uint32_t bar) {
  asm volatile("cp.async.bulk.tensor.3d.shared::cluster.global.mbarrier::complete_tx::bytes [%0], [%1, {%3, %4, %5}], [%2];"
               ::"r"(dst), "l"(m), "r"(bar), "r"(c0), "r"(c1), "r"(c2) : "memory");
}
__device__ __forceinline__ void bulk_load(uint32_t dst, const void* src, uint32_t bytes, uint32_t bar) {
  asm volatile("cp.async.bulk.shared::cluster.global.mbarrier::complete_tx::bytes [%0], [%1], %2, [%3];" ::"r"(dst), "l"(src), "r"(bytes), "r"(bar) : "memory");
}
__device__ __forceinline__ void bulk_store(void* dst, uint32_t src, uint32_t bytes) {
  asm volatile("cp.async.bulk.global.shared::cta.bulk_group [%0], [%1], %2;" ::"l"(dst), "r"(src), "r"(bytes) : "memory");
}
__device__ __forceinline__ void bulk_push(uint32_t dst, uint32_t src, uint32_t bytes, uint32_t bar) {
  asm volatile("cp.async.bulk.shared::cluster.shared::cta.mbarrier::complete_tx::bytes [%0], [%1], %2, [%3];" ::"r"(dst), "r"(src), "r"(bytes), "r"(bar) : "memory");
}
__device__ __forceinline__ void bulk_commit() { asm volatile("cp.async.bulk.commit_group;" ::: "memory"); }
__device__ __forceinline__ void bulk_prefetch(const void* p, uint32_t bytes) {
  asm volatile("cp.async.bulk.prefetch.L2.global [%0], %1;" ::"l"(p), "r"(bytes) : "memory");
}
__device__ __forceinline__ void tma2d_store(const CUtensorMap* m, uint32_t src, int c0, int c1) {
  asm volatile("cp.async.bulk.tensor.2d.global.shared::cta.bulk_group [%0, {%2, %3}], [%1];" ::"l"(m), "r"(src), "r"(c0), "r"(c1) : "memory");
}
__device__ __forceinline__ void wg_fence() { asm volatile("wgmma.fence.sync.aligned;" ::: "memory"); }
__device__ __forceinline__ void wg_commit() { asm volatile("wgmma.commit_group.sync.aligned;" ::: "memory"); }
template <int N> __device__ __forceinline__ void wg_wait() { asm volatile("wgmma.wait_group.sync.aligned %0;" ::"n"(N) : "memory"); }
__device__ __forceinline__ void fence_async_smem() { asm volatile("fence.proxy.async.shared::cta;" ::: "memory"); }
__device__ __forceinline__ void fence_async_global() { asm volatile("fence.proxy.async.global;" ::: "memory"); }
__device__ __forceinline__ void fence_release() { asm volatile("fence.release.gpu;" ::: "memory"); }
__device__ __forceinline__ void fence_acquire() { asm volatile("fence.acquire.gpu;" ::: "memory"); }
__device__ __forceinline__ void nb_sync(int id, int n) { asm volatile("bar.sync %0, %1;" ::"r"(id), "r"(n) : "memory"); }
__device__ __forceinline__ void nb_arrive(int id, int n) { asm volatile("bar.arrive %0, %1;" ::"r"(id), "r"(n) : "memory"); }
__device__ __forceinline__ void stsm4(uint32_t addr, uint32_t r0, uint32_t r1, uint32_t r2, uint32_t r3) {
  asm volatile("stmatrix.sync.aligned.m8n8.x4.shared.b16 [%0], {%1, %2, %3, %4};" ::"r"(addr), "r"(r0), "r"(r1), "r"(r2), "r"(r3) : "memory");
}
__device__ __forceinline__ void sts128(uint32_t addr, uint32_t a, uint32_t b, uint32_t c, uint32_t d) {
  asm volatile("st.shared.v4.b32 [%0], {%1, %2, %3, %4};" ::"r"(addr), "r"(a), "r"(b), "r"(c), "r"(d) : "memory");
}
__device__ __forceinline__ uint32_t pack2(float lo, float hi) {
  uint32_t r; asm("cvt.rn.bf16x2.f32 %0, %1, %2;" : "=r"(r) : "f"(hi), "f"(lo)); return r;
}
__device__ __forceinline__ float bf_lo(uint32_t v) { return __uint_as_float(v << 16); }
__device__ __forceinline__ float bf_hi(uint32_t v) { return __uint_as_float(v & 0xffff0000u); }
__device__ __forceinline__ float bf_round(float v) { return __bfloat162float(__float2bfloat16_rn(v)); }
__device__ __forceinline__ void ldsm4(uint32_t addr, uint32_t (&r)[4]) {
  asm volatile("ldmatrix.sync.aligned.m8n8.x4.shared.b16 {%0, %1, %2, %3}, [%4];" : "=r"(r[0]), "=r"(r[1]), "=r"(r[2]), "=r"(r[3]) : "r"(addr) : "memory");
}
__device__ __forceinline__ uint4 lds128(uint32_t addr) {
  uint4 v; asm volatile("ld.volatile.shared.v4.u32 {%0, %1, %2, %3}, [%4];" : "=r"(v.x), "=r"(v.y), "=r"(v.z), "=r"(v.w) : "r"(addr) : "memory"); return v;
}
__device__ __forceinline__ uint2 lds64(uint32_t addr) { uint2 v; asm volatile("ld.volatile.shared.v2.u32 {%0, %1}, [%2];" : "=r"(v.x), "=r"(v.y) : "r"(addr) : "memory"); return v; }
__device__ __forceinline__ uint32_t lds32(uint32_t addr) { uint32_t v; asm volatile("ld.volatile.shared.u32 %0, [%1];" : "=r"(v) : "r"(addr) : "memory"); return v; }
__device__ __forceinline__ void sts32(uint32_t addr, uint32_t v) { asm volatile("st.shared.u32 [%0], %1;" ::"r"(addr), "r"(v) : "memory"); }
__device__ __forceinline__ uint32_t fma_bf2(uint32_t a, uint32_t b, uint32_t c) { uint32_t r; asm("fma.rn.bf16x2 %0, %1, %2, %3;" : "=r"(r) : "r"(a), "r"(b), "r"(c)); return r; }
__device__ __forceinline__ unsigned ld_relaxed(const unsigned* p) { unsigned v; asm volatile("ld.relaxed.gpu.global.u32 %0, [%1];" : "=r"(v) : "l"(p) : "memory"); return v; }
__device__ __forceinline__ void st_relaxed(unsigned* p, unsigned v) { asm volatile("st.relaxed.gpu.global.u32 [%0], %1;" ::"l"(p), "r"(v) : "memory"); }
__device__ __forceinline__ uint4 ld_relaxed4(const void* p) {
  uint4 v; asm volatile("ld.relaxed.gpu.global.v4.u32 {%0, %1, %2, %3}, [%4];" : "=r"(v.x), "=r"(v.y), "=r"(v.z), "=r"(v.w) : "l"(p) : "memory"); return v;
}
__device__ __forceinline__ float4 ld_relaxed_f4(const void* p) {
  float4 v; asm volatile("ld.relaxed.gpu.global.v4.f32 {%0, %1, %2, %3}, [%4];" : "=f"(v.x), "=f"(v.y), "=f"(v.z), "=f"(v.w) : "l"(p) : "memory"); return v;
}
__device__ __forceinline__ void red_add4(void* p, float a, float b, float c, float d) {
  asm volatile("red.relaxed.gpu.global.add.v4.f32 [%0], {%1, %2, %3, %4};" ::"l"(p), "f"(a), "f"(b), "f"(c), "f"(d) : "memory");
}
__device__ __forceinline__ void red_add(unsigned* p, unsigned v) { asm volatile("red.relaxed.gpu.global.add.u32 [%0], %1;" ::"l"(p), "r"(v) : "memory"); }
__device__ __forceinline__ void wait_counter(const unsigned* p, unsigned target) {
  while (ld_relaxed(p) < target) __nanosleep(32);
  fence_acquire();
}
__device__ __forceinline__ float rcp(float v) { float r; asm("rcp.approx.ftz.f32 %0, %1;" : "=f"(r) : "f"(v)); return r; }
__device__ __forceinline__ float sigmoidf_(float v) { return rcp(1.f + __expf(-v)); }
__device__ __forceinline__ uint32_t phi2(float a, float b, float l2e = 1.4426950408889634f) {
  float ea, eb;
  asm("ex2.approx.ftz.f32 %0, %1;" : "=f"(ea) : "f"(a * l2e));
  asm("ex2.approx.ftz.f32 %0, %1;" : "=f"(eb) : "f"(b * l2e));
  uint32_t t = pack2(a, b), e = pack2(ea, eb), r;
  asm("max.NaN.bf16x2 %0, %0, %1;" : "+r"(t) : "r"(0x35863586u));
  asm("min.bf16x2 %0, %0, %1;" : "+r"(e) : "r"(0x3F803F80u));
  asm("add.rn.bf16x2 %0, %1, %2;" : "=r"(r) : "r"(t), "r"(e));
  return r;
}
__device__ __forceinline__ uint32_t mkdesc(uint32_t addr, uint32_t lbo) { return ((addr & 0x3FFFF) >> 4) | ((lbo >> 4) << 16); }

__device__ __forceinline__ void mma_qkv(float (&d)[96], uint32_t da, uint32_t db, int sc) {
  asm volatile("{\n.reg .pred p;\n.reg .b64 da, db;\nmov.b64 da, {%96, 0x40000040};\nmov.b64 db, {%97, 0x40000040};\nsetp.ne.b32 p, %98, 0;\n"
    "wgmma.mma_async.sync.aligned.m64n192k16.f32.bf16.bf16 "
    "{%0,%1,%2,%3,%4,%5,%6,%7,%8,%9,%10,%11,%12,%13,%14,%15,%16,%17,%18,%19,%20,%21,%22,%23,"
    "%24,%25,%26,%27,%28,%29,%30,%31,%32,%33,%34,%35,%36,%37,%38,%39,%40,%41,%42,%43,%44,%45,%46,%47,"
    "%48,%49,%50,%51,%52,%53,%54,%55,%56,%57,%58,%59,%60,%61,%62,%63,%64,%65,%66,%67,%68,%69,%70,%71,"
    "%72,%73,%74,%75,%76,%77,%78,%79,%80,%81,%82,%83,%84,%85,%86,%87,%88,%89,%90,%91,%92,%93,%94,%95}, "
    "da, db, p, 1, 1, 0, 1;\n}\n"
    : "+f"(d[0]), "+f"(d[1]), "+f"(d[2]), "+f"(d[3]), "+f"(d[4]), "+f"(d[5]), "+f"(d[6]), "+f"(d[7]),
      "+f"(d[8]), "+f"(d[9]), "+f"(d[10]), "+f"(d[11]), "+f"(d[12]), "+f"(d[13]), "+f"(d[14]), "+f"(d[15]),
      "+f"(d[16]), "+f"(d[17]), "+f"(d[18]), "+f"(d[19]), "+f"(d[20]), "+f"(d[21]), "+f"(d[22]), "+f"(d[23]),
      "+f"(d[24]), "+f"(d[25]), "+f"(d[26]), "+f"(d[27]), "+f"(d[28]), "+f"(d[29]), "+f"(d[30]), "+f"(d[31]),
      "+f"(d[32]), "+f"(d[33]), "+f"(d[34]), "+f"(d[35]), "+f"(d[36]), "+f"(d[37]), "+f"(d[38]), "+f"(d[39]),
      "+f"(d[40]), "+f"(d[41]), "+f"(d[42]), "+f"(d[43]), "+f"(d[44]), "+f"(d[45]), "+f"(d[46]), "+f"(d[47]),
      "+f"(d[48]), "+f"(d[49]), "+f"(d[50]), "+f"(d[51]), "+f"(d[52]), "+f"(d[53]), "+f"(d[54]), "+f"(d[55]),
      "+f"(d[56]), "+f"(d[57]), "+f"(d[58]), "+f"(d[59]), "+f"(d[60]), "+f"(d[61]), "+f"(d[62]), "+f"(d[63]),
      "+f"(d[64]), "+f"(d[65]), "+f"(d[66]), "+f"(d[67]), "+f"(d[68]), "+f"(d[69]), "+f"(d[70]), "+f"(d[71]),
      "+f"(d[72]), "+f"(d[73]), "+f"(d[74]), "+f"(d[75]), "+f"(d[76]), "+f"(d[77]), "+f"(d[78]), "+f"(d[79]),
      "+f"(d[80]), "+f"(d[81]), "+f"(d[82]), "+f"(d[83]), "+f"(d[84]), "+f"(d[85]), "+f"(d[86]), "+f"(d[87]),
      "+f"(d[88]), "+f"(d[89]), "+f"(d[90]), "+f"(d[91]), "+f"(d[92]), "+f"(d[93]), "+f"(d[94]), "+f"(d[95])
    : "r"(da), "r"(db), "r"(sc));
}

__device__ __forceinline__ void mma_out(float (&d)[64], uint32_t da, uint32_t db, int sc) {
  asm volatile("{\n.reg .pred p;\n.reg .b64 da, db;\nmov.b64 da, {%64, 0x40000040};\nmov.b64 db, {%65, 0x40000040};\nsetp.ne.b32 p, %66, 0;\n"
    "wgmma.mma_async.sync.aligned.m64n128k16.f32.bf16.bf16 "
    "{%0,%1,%2,%3,%4,%5,%6,%7,%8,%9,%10,%11,%12,%13,%14,%15,%16,%17,%18,%19,%20,%21,%22,%23,"
    "%24,%25,%26,%27,%28,%29,%30,%31,%32,%33,%34,%35,%36,%37,%38,%39,%40,%41,%42,%43,%44,%45,%46,%47,"
    "%48,%49,%50,%51,%52,%53,%54,%55,%56,%57,%58,%59,%60,%61,%62,%63}, "
    "da, db, p, 1, 1, 0, 1;\n}\n"
    : "+f"(d[0]), "+f"(d[1]), "+f"(d[2]), "+f"(d[3]), "+f"(d[4]), "+f"(d[5]), "+f"(d[6]), "+f"(d[7]),
      "+f"(d[8]), "+f"(d[9]), "+f"(d[10]), "+f"(d[11]), "+f"(d[12]), "+f"(d[13]), "+f"(d[14]), "+f"(d[15]),
      "+f"(d[16]), "+f"(d[17]), "+f"(d[18]), "+f"(d[19]), "+f"(d[20]), "+f"(d[21]), "+f"(d[22]), "+f"(d[23]),
      "+f"(d[24]), "+f"(d[25]), "+f"(d[26]), "+f"(d[27]), "+f"(d[28]), "+f"(d[29]), "+f"(d[30]), "+f"(d[31]),
      "+f"(d[32]), "+f"(d[33]), "+f"(d[34]), "+f"(d[35]), "+f"(d[36]), "+f"(d[37]), "+f"(d[38]), "+f"(d[39]),
      "+f"(d[40]), "+f"(d[41]), "+f"(d[42]), "+f"(d[43]), "+f"(d[44]), "+f"(d[45]), "+f"(d[46]), "+f"(d[47]),
      "+f"(d[48]), "+f"(d[49]), "+f"(d[50]), "+f"(d[51]), "+f"(d[52]), "+f"(d[53]), "+f"(d[54]), "+f"(d[55]),
      "+f"(d[56]), "+f"(d[57]), "+f"(d[58]), "+f"(d[59]), "+f"(d[60]), "+f"(d[61]), "+f"(d[62]), "+f"(d[63])
    : "r"(da), "r"(db), "r"(sc));
}

__device__ __forceinline__ void mma_ktv(float (&d)[36], uint32_t da, uint32_t db, int sc) {
  asm volatile("{\n.reg .pred p;\n.reg .b64 da, db;\nmov.b64 da, {%36, 0x40000040};\nmov.b64 db, {%37, 0x40000040};\nsetp.ne.b32 p, %38, 0;\n"
    "wgmma.mma_async.sync.aligned.m64n72k16.f32.bf16.bf16 "
    "{%0,%1,%2,%3,%4,%5,%6,%7,%8,%9,%10,%11,%12,%13,%14,%15,%16,%17,%18,%19,%20,%21,%22,%23,"
    "%24,%25,%26,%27,%28,%29,%30,%31,%32,%33,%34,%35}, "
    "da, db, p, 1, 1, 1, 1;\n}\n"
    : "+f"(d[0]), "+f"(d[1]), "+f"(d[2]), "+f"(d[3]), "+f"(d[4]), "+f"(d[5]), "+f"(d[6]), "+f"(d[7]),
      "+f"(d[8]), "+f"(d[9]), "+f"(d[10]), "+f"(d[11]), "+f"(d[12]), "+f"(d[13]), "+f"(d[14]), "+f"(d[15]),
      "+f"(d[16]), "+f"(d[17]), "+f"(d[18]), "+f"(d[19]), "+f"(d[20]), "+f"(d[21]), "+f"(d[22]), "+f"(d[23]),
      "+f"(d[24]), "+f"(d[25]), "+f"(d[26]), "+f"(d[27]), "+f"(d[28]), "+f"(d[29]), "+f"(d[30]), "+f"(d[31]),
      "+f"(d[32]), "+f"(d[33]), "+f"(d[34]), "+f"(d[35])
    : "r"(da), "r"(db), "r"(sc));
}

__device__ __forceinline__ void mma_qkvz(float (&d)[20], const uint32_t (&a)[4], uint32_t db, int sc) {
  asm volatile("{\n.reg .pred p;\n.reg .b64 db;\nmov.b64 db, {%24, 0x20};\nsetp.ne.b32 p, %25, 0;\n"
    "wgmma.mma_async.sync.aligned.m64n40k16.f32.bf16.bf16 "
    "{%0,%1,%2,%3,%4,%5,%6,%7,%8,%9,%10,%11,%12,%13,%14,%15,%16,%17,%18,%19}, "
    "{%20,%21,%22,%23}, db, p, 1, 1, 1;\n}\n"
    : "+f"(d[0]), "+f"(d[1]), "+f"(d[2]), "+f"(d[3]), "+f"(d[4]), "+f"(d[5]), "+f"(d[6]), "+f"(d[7]),
      "+f"(d[8]), "+f"(d[9]), "+f"(d[10]), "+f"(d[11]), "+f"(d[12]), "+f"(d[13]), "+f"(d[14]), "+f"(d[15]),
      "+f"(d[16]), "+f"(d[17]), "+f"(d[18]), "+f"(d[19])
    : "r"(a[0]), "r"(a[1]), "r"(a[2]), "r"(a[3]), "r"(db), "r"(sc));
}

struct Params {
  CUtensorMap x, w, xr, wo, out, gate, up, down;
};

__device__ __forceinline__ void fma8(float (&acc)[8], const uint4& w, float m) {
  acc[0] = fmaf(bf_lo(w.x), m, acc[0]); acc[1] = fmaf(bf_hi(w.x), m, acc[1]);
  acc[2] = fmaf(bf_lo(w.y), m, acc[2]); acc[3] = fmaf(bf_hi(w.y), m, acc[3]);
  acc[4] = fmaf(bf_lo(w.z), m, acc[4]); acc[5] = fmaf(bf_hi(w.z), m, acc[5]);
  acc[6] = fmaf(bf_lo(w.w), m, acc[6]); acc[7] = fmaf(bf_hi(w.w), m, acc[7]);
}
__device__ __forceinline__ float butterfly8(float (&s)[8], int lane, int o) {
#pragma unroll
  for (int k = 1; k < 8; k <<= 1) {
    const bool up = lane & (o * k);
#pragma unroll
    for (int j = 0; j < 4 / k; j++) s[j] = (up ? s[2 * j + 1] : s[2 * j]) + __shfl_xor_sync(~0u, up ? s[2 * j] : s[2 * j + 1], o * k);
  }
  return s[0];
}
constexpr int PEER = 9;
constexpr __host__ __device__ uint32_t step_list() {
  uint32_t r = 0;
  for (int j = PEER - 1; j >= 0; j--) if (j != OWN) r = r << 4 | j % 5 | (j < 5) << 3;
  return r;
}
template <bool BY_SM> struct Tile {
  int sm, tm, tn, mu;
  bool spare;
  __device__ __forceinline__ Tile() {
    if (BY_SM) asm volatile("mov.u32 %0, %%smid;" : "=r"(sm));
    else sm = blockIdx.x + (blockIdx.x >= 120) * 4;
    const int tp = sm >> 1, pr = sm & 1;
    const int v = tp < 32 ? tp : tp < 60 ? (tp * 293 - 928) >> 8 : tp * 8 - 464, g = v & 7, i = v >> 3;
    const int j = i * 11 >> 5, c = i - j * 3;
    if (MAP == 0) { tm = (v & 6) * 2 + (i & 3); tn = (v & 1) * 4 + (v >> 4 & 2) + pr; }
    if (MAP == 1) { tm = (v & 6) * 2 + (c < 2 ? j : 3); tn = (v & 1) * 4 + (c < 2 ? c : j) * 2 + pr; }
    mu = i == NOMOD ? 112 : g * 14 + (i - (i > NOMOD)) * 2 + pr;
    spare = (tp | 1) == 61;
  }
};

template <bool BY_SM> __global__ void __cluster_dims__(2, 1, 1) __launch_bounds__(NTHREADS, 1) fused_kernel(const __nv_bfloat16* __restrict__ px, Scratch* gs, const __nv_bfloat16* __restrict__ w_gate,
             const __nv_bfloat16* __restrict__ w_up, const __nv_bfloat16* __restrict__ w_r, const __nv_bfloat16* __restrict__ gate_w,
             const __grid_constant__ Params p) {
  extern __shared__ __align__(1024) uint8_t smem[];
  const uint32_t sb = __shfl_sync(~0u, (uint32_t)__cvta_generic_to_shared(smem), 0);
  const int tid = threadIdx.x, lane = tid & 31;
  const int warp = __shfl_sync(~0u, tid >> 5, 0), wg = warp >> 2;
  const uint32_t t_start = clock32();
  const Tile<BY_SM> tile;
  const int tm = tile.tm, tn = tile.tn, mu = tile.mu, cta = tm * 8 + tn;
#define KX 0
  const int kx = KX == 1 ? (tn & 4) * 16 : KX == 2 ? (tn & 6) * 32 : KX == 3 ? (tn & 4) * 32 : KX == 4 ? (tn & 4) * 128 : KX == 5 ? (tn & 4) * 16 : 0;
  const int kx0 = KX == 5 ? 0 : KX == 6 ? (tn & 4) * 16 : kx;
  {
    const uint32_t cnt = (uint32_t)((warp & 8 ? bar_counts(16) : bar_counts(0)) >> (warp & 7) * 8);
    if (elect()) mbar_init(sb + OFF_BAR + warp * 16, cnt & 15);
    if (elect()) mbar_init(sb + OFF_BAR + warp * 16 + 8, cnt >> 4 & 15);
    if (elect()) mbar_init(sb + BAR_LAND + warp * 8, 1);
    asm volatile("fence.mbarrier_init.release.cluster;" ::: "memory");
  }
  if (warp == 0 && !tile.spare) {
#pragma unroll
    for (int s = 0; s < PRE; s++) {
      if (elect()) tma3d(sb + OFF_RING + s * STAGE_BYTES + A_BYTES, &p.w, tn * 64, s * 64 ^ kx0, 0, sb + BAR_FULL + s * 8);
      if (elect()) tma2d(sb + OFF_RING + s * STAGE_BYTES, &p.x, s * 64 ^ kx0, tm * 128, sb + BAR_FULL + s * 8);
      PROF_P(lane == 0, 64 + s);
    }
    if (elect()) {
#pragma unroll
      for (int s = 0; s < PRE; s++) { mbar_expect_tx(sb + BAR_FULL + s * 8, STAGE_BYTES); mbar_arrive(sb + BAR_FULL + s * 8); }
    }
  }
  asm volatile("" ::: "memory");
  if (warp == 5) {
#pragma unroll
    for (int i = 0; i < 4; i++) sts128(sb + OFF_ONES + i * 512 + lane * 16, 0x3F803F80u, 0x3F803F80u, 0x3F803F80u, 0x3F803F80u);
    sts32(sb + OFF_MISC + 20, 0x3FB8AA3Bu);
    fence_async_smem();
  }
  __syncthreads();
  if (tile.spare) {
    if (warp == 0) {
      const unsigned tag = (ld_relaxed(&gs->spare[tile.sm & 3]) + 1) & 0xFFF;
      const unsigned long long t0 = gtime();
      uint4 r4;
      do {
        __nanosleep(2048);
        if (gtime() - t0 > WATCHDOG_NS) __trap();
        r4 = ld_relaxed4(&gs->rslot[tile.sm & 3][lane * 4]);
      } while (!__all_sync(~0u, (((r4.x ^ tag) | (r4.y ^ tag) | (r4.z ^ tag) | (r4.w ^ tag)) & 0xFFF) == 0));
      if (tid == 0) st_relaxed(&gs->spare[tile.sm & 3], tag);
    }
    return;
  }

  if (wg == 3) {
    asm volatile("setmaxnreg.dec.sync.aligned.u32 24;");
    if (warp == 12) {
      mbar_wait(sb + BAR_W31, 0);
      mbar_wait(sb + BAR_IDX, 0);
      const uint32_t lowb = (1u << (tn & 6) * 4) - 1;
      uint32_t slabs = 0x76543210u, steps = step_list();
      const uint4* src = gs->o[tm][0];
      unsigned seen = AFLAG ? 0 : ~0u;
      if (!AFLAG) mbar_wait(sb + BAR_EMPTY + AW * 8, 1);
#pragma unroll 1
      for (int n = 8; n >= 6; n -= 2) {
#pragma unroll 1
        for (int i = 0; i < n; i++, slabs >>= 4, steps >>= 4) {
          const uint32_t s = steps & 7, full = sb + BAR_FULL + s * 8, need = 4u << (slabs & 7) * 4;
          const uint32_t land = n == 8 ? full : sb + BAR_LAND + i * 8;
          mbar_wait(full + (BAR_EMPTY - BAR_FULL), steps >> 3 & 1);
          PROF(lane == 0 && (!PROFC || n == 6), 224 + i + (n == 6) * 10);
          if (AFLAG && !__all_sync(~0u, seen & need)) {
            while (!__all_sync(~0u, (seen = ld_relaxed(gs->cnt[tm])) & need)) __nanosleep(FSL);
            if (FENCES & 1) fence_acquire();
            if (FENCES & 2) fence_async_global();
          }
          if (elect()) bulk_load(sb + OFF_RING + s * O_BYTES, src + (slabs & 7) * 1024, A_BYTES, land);
          if (elect()) mbar_expect_tx(land, A_BYTES);
          PROF(lane == 0 && (!PROFC || n == 6), 240 + i + (n == 6) * 10);
        }
        slabs = (0x76543210u & lowb) | (0x765432u & ~lowb);
        steps = 0x0CBA98u;
        src += 8 * 1024;
      }
    } else if (warp == 13) {
      uint32_t full = sb + BAR_FULL + PRE * 8, dst = sb + OFF_RING + PRE * STAGE_BYTES + A_BYTES, c0 = tn * 64, c1 = PRE * 64;
#pragma unroll 1
      for (int g = PRE; g < 32; g++) {
        if (g < 4) while ((int)(clock32() - t_start) < g * ST1) {}
        const bool reuse = (g >> 2) == 4;
        mbar_wait(full + (BAR_EMPTY - BAR_FULL), ((g >> 2) & 1) ^ 1);
        if (!reuse && elect()) tma2d(dst - A_BYTES, &p.x, c1 ^ kx, tm * 128, full);
        if (elect()) tma3d(dst, &p.w, c0, c1 ^ kx, 0, full);
        if (elect()) { mbar_expect_tx(full, reuse ? BQ_BYTES : STAGE_BYTES); mbar_arrive(full); }
        PROF_P(lane == 0, 64 + g);
        const uint32_t i = g - RT_G0;
        if (i < 4 && elect()) {
          mbar_expect_tx(sb + BAR_RT + i * 8, i ? 8192 : 8192 + 4096);
          tma2d(sb + OFF_PK + i * 8192, &p.xr, ((i + RT_ROT) & 3) * 256, cta * 16, sb + BAR_RT + i * 8);
          if (i == 0) { bulk_load(sb + OFF_KVB, w_r, 2048, sb + BAR_RT); bulk_load(sb + OFF_KVB + 2048, gate_w, 2048, sb + BAR_RT); }
        }
        const uint32_t c = g - MOD_START;
        if (c == MOD_BUFS) mbar_wait(sb + BAR_RTD, 0);
        if (c < MOD_BUFS0 && mu < MOD_CTAS && elect()) {
          PROF_P(true, 192 + c);
          const uint32_t mfull = sb + BAR_MFULL + c * 8, mdst = sb + OFF_MOD + c * 8192;
          mbar_expect_tx(mfull, c ? 8192 : 8192 + 2048);
          tma3d(mdst, &p.gate, mu * 32, c * 16, 0, mfull); tma3d(mdst + 4096, &p.up, mu * 32, c * 16, 0, mfull);
        }
        const uint32_t pc = g - PF_MOD;
        if (pc < 16 && elect()) bulk_prefetch((cta & 64 ? w_up : w_gate) + (size_t)(pc * 64 + (cta & 63)) * F_, F_ * 2);
        full += 8; dst += STAGE_BYTES; c1 += 64;
        if ((g & 3) == 3) { full -= 32; dst -= 4 * STAGE_BYTES; }
        if (g == 15) { c0 += 512; c1 = 768; }
        if (g == 19) c1 = 0;
      }
      mbar_arrive_warp(sb + BAR_W31);
      const uint32_t lowb = (1u << (tn & 6) * 4) - 1;
      uint64_t slabs = (uint64_t)((0xFEDCBA98u & lowb) | (0xFEDCBAu & ~lowb)) << 40 | (uint64_t)(8 + (tn ^ 1)) << 36 | (uint64_t)(8 + tn) << OWN * 4 |
                       (0x76543210ull & ~(~0ull << OWN * 4)) | (0x765432100ull & ~0ull << (OWN * 4 + 4));
      uint32_t ph = 1;
      c1 = 0;
#pragma unroll 1
      for (int g = 0; g < 16; g++) {
        mbar_wait(full + (BAR_EMPTY - BAR_FULL), ph);
        if (elect()) tma3d(dst, &p.wo, 0, c1, tn * 2, full);
        if (elect()) mbar_expect_tx(full, BO_BYTES);
        PROF_P(lane == 0, 96 + g);
        if (g == OWN && elect()) mbar_arrive(full);
        full += 8; dst += O_BYTES; slabs >>= 4; c1 = ((uint32_t)slabs & 15) * 64;
        if (full == sb + BAR_EMPTY) { full -= 40; dst -= 5 * O_BYTES; ph ^= 1; }
      }
    } else if (warp == 14) {
      if (mu < MOD_CTAS) {
        uint32_t full = sb + BAR_MFULL, dst = sb + OFF_MOD, ph = 0;
#pragma unroll 1
        for (int c = MOD_BUFS0; c < 24; c++) {
          mbar_wait(full + (BAR_MEMPTY - BAR_MFULL), ph);
          PROF_P(lane == 0, 192 + c);
          if (c < 16) {
            if (elect()) { tma3d(dst, &p.gate, mu * 32, c * 16, 0, full); tma3d(dst + 4096, &p.up, mu * 32, c * 16, 0, full); }
          } else if (elect()) tma3d(dst, &p.down, 0, mu * 32 + (c - 16) * 4, 0, full);
          if (elect()) mbar_expect_tx(full, 8192);
          full += 8; dst += 8192;
          if (dst == sb + OFF_PK) { full -= MOD_BUFS * 8; dst = sb + OFF_MOD; ph ^= 1; }
        }
      }
      if (elect()) {
      mbar_wait(sb + BAR_IDX, 0);
      const bool paired = PAIRED && ld_relaxed(&gs->block[cta ^ 1]) == (blockIdx.x ^ 1);
      const uint32_t pb = peer_addr(sb);
      mbar_wait(sb + BAR_EMPTY + PEER % 5 * 8, 0);
      mbar_expect_tx(sb + BAR_FULL + PEER % 5 * 8, A_BYTES);
      if (paired) mbar_arrive_peer(pb + BAR_PA);
      mbar_wait(sb + BAR_OST, 0);
      mbar_expect_tx(sb + BAR_X, 32768);
      tma2d(sb + OFF_PK, &p.x, tn * 128, tm * 128, sb + BAR_X);
      tma2d(sb + OFF_V, &p.x, tn * 128 + 64, tm * 128, sb + BAR_X);
      if (paired) {
        mbar_wait(sb + BAR_PA, 0);
        mbar_wait(sb + BAR_OWN, 0);
        bulk_push(pb + OFF_RING + PEER % 5 * O_BYTES, sb + OFF_MOD, A_BYTES, pb + BAR_FULL + PEER % 5 * 8);
        mbar_wait(sb + BAR_EMPTY + PEER % 5 * 8, 1);
        mbar_arrive_peer(pb + BAR_PA);
        mbar_wait(sb + BAR_PA, 1);
      } else {
        mbar_wait(sb + BAR_OWN, 0);
        __nanosleep(500);
        bulk_load(sb + OFF_RING + PEER % 5 * O_BYTES, gs->o[tm][8 + (tn ^ 1)], A_BYTES, sb + BAR_FULL + PEER % 5 * 8);
      }
      }
    } else if (elect()) {
#pragma unroll 1
      for (int i = 2; i < 8; i++) asm volatile("prefetch.tensormap [%0];" ::"l"(&p.x + i) : "memory");
      mbar_wait_bounded(sb + BAR_DONE, 0);
    }
  } else if (wg == 2) {
    asm volatile("setmaxnreg.dec.sync.aligned.u32 40;");
    const int mw = warp & 3;
    if (mw == 0) {
      const unsigned tag = (ld_relaxed(&gs->rslot[tn][cta]) + 1) & 0xFFF;
#pragma unroll
      for (int i = 0; i < 4; i++)
        if (lane < NCLR) ((float4*)gs)[cta * (NCLR * 4) + i * NCLR + lane] = make_float4(0.f, 0.f, 0.f, 0.f);
      if (lane == 29) gs->block[cta] = blockIdx.x;
      fence_release();
      nb_sync(NB_KEY, 160);
      const uint4 k4 = lds128(sb + OFF_MISC);
      if (lane < 8) st_relaxed(&gs->rslot[lane][cta], max(max(k4.x, k4.y), max(k4.z, k4.w)) | tag);
      if (lane < 16) st_relaxed(&gs->gslot[cta * 16 + lane], lds32(sb + OFF_G + lane * 4) | tag);
      PROF(lane == 0, 20);
      uint4 r4;
      do {
        __nanosleep(RT_SLEEP);
        r4 = ld_relaxed4(&gs->rslot[tn][lane * 4]);
      } while (!__all_sync(~0u, (((r4.x ^ tag) | (r4.y ^ tag) | (r4.z ^ tag) | (r4.w ^ tag)) & 0xFFF) == 0));
      const int c0 = 0xFFF0 - lane * 64;
      unsigned key = max(max((r4.x & 0xFFFF0000u) | (c0 + ((r4.x >> 12) & 15)), (r4.y & 0xFFFF0000u) | (c0 - 16 + ((r4.y >> 12) & 15))),
                         max((r4.z & 0xFFFF0000u) | (c0 - 32 + ((r4.z >> 12) & 15)), (r4.w & 0xFFFF0000u) | (c0 - 48 + ((r4.w >> 12) & 15))));
      key = __reduce_max_sync(~0u, key);
      if (elect()) {
        sts32(sb + OFF_MISC + 16, key);
        sts32(sb + OFF_MISC + 24, tag & 1);
        if (mu < MOD_CTAS) bulk_load(sb + OFF_XSEL, px + (size_t)(0xFFFF - (key & 0xFFFF)) * D_, 2048, sb + BAR_MFULL);
      }
      PROF(lane == 0, 21);
      do {
        r4 = ld_relaxed4(&gs->gslot[tm * 128 + lane * 4]);
      } while (!__all_sync(~0u, (((r4.x ^ tag) | (r4.y ^ tag) | (r4.z ^ tag) | (r4.w ^ tag)) & 0xFFF) == 0));
      sts128(sb + OFF_G + lane * 16, r4.x & 0xFFFF0000u, r4.y & 0xFFFF0000u, r4.z & 0xFFFF0000u, r4.w & 0xFFFF0000u);
      fence_acquire();
      __syncwarp();
      mbar_arrive_warp(sb + BAR_IDX);
    }
    PROF(tid == 256, 22);
    if (mu >= MOD_CTAS) {
      mbar_arrive_warp(sb + BAR_IDX);
      mbar_arrive_warp(sb + BAR_OA);
    } else {
      const uint32_t wp = sb + OFF_MOD + (mw >> 1) * 4096 + (mw & 1) * 512 + lane * 16;
      uint32_t mp = sb + OFF_XSEL - 128 + (mw & 1) * 64 + (lane >> 2) * 8, mc = 128;
      float acc[8] = {0.f, 0.f, 0.f, 0.f, 0.f, 0.f, 0.f, 0.f};
      uint32_t b = ~0u, ph = 0, a = sb + OFF_ONES - 3072;
      float m3 = 0.f;
      const uint32_t zero = lds32(sb + OFF_ONES) & 1;
      uint2 m = make_uint2(0, 0);
      uint4 w0 = make_uint4(0, 0, 0, 0), w1 = w0, w2 = w0, w3 = w0;
#pragma unroll 1
      for (int c = -1;; c++) {
        fma8(acc, w3, m3);
        w3 = lds128(a + 3072);
        const uint32_t rel = sb + BAR_MEMPTY + (MX > 1 ? ((0x4444210u ^ 7u << (MOD_BUFS0 - 1) * 4) >> b * 4 & 15) : b) * 8;
        if (!FIXR && c >= 0) mbar_arrive_warp(rel);
        if (c == 16) {
          const uint32_t ft = fresh_tid(), fl = ft & 31;
          sts32(sb + OFF_PART + (ft & 96) * 4 + ((ft & 3) * 8 + (fl >> 2)) * 4, __float_as_uint(butterfly8(acc, fl, 4)));
          nb_sync(NB_MODW, 128);
          const float* part = (const float*)(smem + OFF_PART) + fl;
          const float gp = bf_round(part[0] + part[32]), up = bf_round(part[64] + part[96]);
          *(__nv_bfloat16*)(smem + OFF_PART + 512 + fl * 2) = __float2bfloat16_rn(bf_round(gp * sigmoidf_(gp)) * up);
          __syncwarp();
          mp = sb + OFF_PART + 512; mc = 8;
          m = lds64(mp);
#pragma unroll
          for (int i = 0; i < 8; i++) acc[i] = 0.f;
          PROF(lane == 0 && mw == 0, 23);
        }
        if (++b == (c < MOD_BUFS0 ? MOD_BUFS0 : MOD_BUFS)) { b = 0; ph ^= 1; }
        const uint32_t ok = mbar_test(sb + BAR_MFULL + b * 8, ph);
        fma8(acc, w0, bf_lo(m.x));
        if (FIXR == 2 && c >= 0) mbar_arrive_warp(rel + ((w3.x | __float_as_uint(acc[7])) & zero));
        fma8(acc, w1, bf_hi(m.x));
        if (FIXR == 3 && c >= 0) mbar_arrive_warp(rel + ((w3.x | __float_as_uint(acc[7])) & zero));
        fma8(acc, w2, bf_lo(m.y));
        m3 = bf_hi(m.y);
        if (FIXR == 1 && c >= 0) mbar_arrive_warp(rel + (w3.x & zero));
        if (FIXR == 4 && c >= 0) mbar_arrive_warp(rel + ((w3.x | __float_as_uint(acc[7])) & zero));
        if (c == 23) break;
        if (!ok) mbar_wait(sb + BAR_MFULL + b * 8, ph);
        a = wp + b * 8192;
        mp += mc;
        m = lds64(mp);
        w0 = lds128(a); w1 = lds128(a + 1024); w2 = lds128(a + 2048);
      }
      fma8(acc, w3, m3);
      mbar_arrive_warp(sb + BAR_OA);
      float* yacc = gs->y[tn] + (fresh_tid() & 127) * 8;
      red_add4(yacc, acc[0], acc[1], acc[2], acc[3]);
      red_add4(yacc + 4, acc[4], acc[5], acc[6], acc[7]);
      PROF(lane == 0 && mw == 0, 25);
      nb_sync(NB_MODW, 128);
      if (mw == 0 && elect()) { fence_release(); red_add(gs->cnt[32], 1); }
      PROF(lane == 0 && mw == 0, 24);
    }
    const unsigned key = lds32(sb + OFF_MISC + 16);
    const int sel = 0xFFFF - (int)(key & 0xFFFF) - tm * 128;
    if (mw == 0 && sel >= 0 && sel < 128) {
      if (elect()) wait_counter(gs->cnt[32], MOD_CTAS);
      __syncwarp();
      const unsigned k16 = key >> 16;
      const float rs = bf_round(sigmoidf_(__uint_as_float(((k16 & 0x8000u) ? (k16 & 0x7FFFu) : (~k16 & 0xFFFFu)) << 16)));
      float4 v = make_float4(0.f, 0.f, 0.f, 0.f);
#pragma unroll 4
      for (int i = 0; i < 8; i++) {
        const float4 u = ld_relaxed_f4(gs->y[i] + tn * 128 + lane * 4);
        v.x += u.x; v.y += u.y; v.z += u.z; v.w += u.w;
      }
      mbar_wait(sb + BAR_X, 0);
      uint2* xp = (uint2*)(smem + OFF_PK + (lane >> 4) * 16384 + sel * 128 + ((((lane >> 1) & 7) ^ (sel & 7)) << 4) + (lane & 1) * 8);
      const uint2 xv = *xp;
      *xp = make_uint2(pack2(bf_lo(xv.x) + bf_round(bf_round(v.x) * rs), bf_hi(xv.x) + bf_round(bf_round(v.y) * rs)),
                       pack2(bf_lo(xv.y) + bf_round(bf_round(v.z) * rs), bf_hi(xv.y) + bf_round(bf_round(v.w) * rs)));
      __syncwarp();
      mbar_arrive_warp(sb + BAR_Y);
    }
  } else {
    asm volatile("setmaxnreg.inc.sync.aligned.u32 224;");
    const int w = warp & 3, wt = tid & 127;
    const int nb_self = NB_WG0 + wg;
    const uint32_t da0 = mkdesc(sb + OFF_RING, 16), db0 = mkdesc(sb + OFF_RING + A_BYTES, 8192);

    if (wg == 1) {
      float s[8] = {0.f, 0.f, 0.f, 0.f, 0.f, 0.f, 0.f, 0.f};
      const uint32_t zero = lds32(sb + OFF_ONES) & 1;
      uint32_t mask = 0xffff0000u;
#pragma unroll 1
      for (int i = 0; i < 4; i++) {
        const uint32_t u = (i + RT_ROT) & 3;
        mbar_wait(sb + BAR_RT + i * 8, 0);
        const uint4 wr = lds128(sb + OFF_KVB + u * 512 + lane * 16), gw = lds128(sb + OFF_KVB + 2048 + u * 512 + lane * 16);
        uint4 xv[4];
#pragma unroll
        for (int r = 0; r < 4; r++) xv[r] = lds128(sb + OFF_PK + i * 8192 + (w * 4 + r) * 512 + lane * 16);
        const float wf[16] = {bf_lo(wr.x), bf_hi(wr.x), bf_lo(wr.y), bf_hi(wr.y), bf_lo(wr.z), bf_hi(wr.z), bf_lo(wr.w), bf_hi(wr.w),
                              bf_lo(gw.x), bf_hi(gw.x), bf_lo(gw.y), bf_hi(gw.y), bf_lo(gw.z), bf_hi(gw.z), bf_lo(gw.w), bf_hi(gw.w)};
#pragma unroll
        for (int r = 0; r < 4; r++) {
          const uint4 xq = xv[r];
          const float xf[8] = {bf_lo(xq.x), __uint_as_float(xq.x & mask), bf_lo(xq.y), bf_hi(xq.y), bf_lo(xq.z), bf_hi(xq.z), bf_lo(xq.w), bf_hi(xq.w)};
#pragma unroll
          for (int j = 0; j < 8; j++) { s[2 * r] = fmaf(xf[j ^ 1], wf[j ^ 1], s[2 * r]); s[2 * r + 1] = fmaf(xf[j ^ 1], wf[8 + (j ^ 1)], s[2 * r + 1]); }
          mask = ((__float_as_uint(s[2 * r]) | __float_as_uint(s[2 * r + 1])) & zero) | 0xffff0000u;
        }
      }
      mbar_arrive_warp(sb + BAR_RTD);
      float v = butterfly8(s, lane, 1);
      PROF_C(wt == 0 && v != 12345.f, 19);
      v += __shfl_xor_sync(~0u, v, 8);
      v = bf_round(v + __shfl_xor_sync(~0u, v, 16));
      const unsigned rb = __float_as_uint(v) >> 16, row = w * 4 + ((lane & 7) >> 1);
      unsigned key = (lane & 1) ? 0u : ((((rb & 0x8000u) ? (~rb & 0xFFFFu) : (rb | 0x8000u)) << 16) | ((15 - row) << 12));
      key = __reduce_max_sync(~0u, key);
      if (lane == 0) sts32(sb + OFF_MISC + w * 4, key);
      if (lane < 8 && (lane & 1)) sts32(sb + OFF_G + row * 4, __float_as_uint(bf_round(sigmoidf_(v))));
      nb_arrive(NB_KEY, 160);
      nb_sync(NB_ORDER_AB, 256);
    }

    uint32_t pq[2][4][4];
    float4* const kvacc = &gs->kv[wg][tn][0][wt];
    {
      float acc[2][96];
      PROF_C(wt == 0, 1 + wg * 8);
#pragma unroll 1
      for (int g = 0; g < (SK > 1 ? 16 - SK : 16); g++) {
        const uint32_t s = g & 3;
        const uint32_t da = da0 + s * (STAGE_BYTES >> 4), db = db0 + s * (STAGE_BYTES >> 4);
        mbar_wait(sb + BAR_FULL + s * 8, (g >> 2) & 1);
        PROF_C(wt == 0, 64 + wg * 16 + g);
#pragma unroll
        for (int m = 0; m < 2; m++) {
          wg_fence();
#pragma unroll
          for (int kk = 0; kk < 4; kk++) mma_qkv(acc[m], da + (m * 512 + kk * 2), db + kk * 128, kk ? 1 : g);
          wg_commit();
          if (m == 0) {
            wg_wait<1>();
            if (g) mbar_arrive_warp(sb + BAR_EMPTY + ((g + 3) & 3) * 8);
          }
        }
      }
      auto half_step = [&](int m, int g) {
        wg_fence();
#pragma unroll
        for (int kk = 0; kk < 4; kk++)
          mma_qkv(acc[m], da0 + ((g & 3) * (STAGE_BYTES >> 4) + m * 512 + kk * 2), db0 + ((g & 3) * (STAGE_BYTES >> 4) + kk * 128), 1);
        wg_commit();
      };
#pragma unroll
      for (int g = 16 - SK; g < 16; g++) {
        mbar_wait(sb + BAR_FULL + (g & 3) * 8, 1);
        PROF_C(wt == 0, 64 + wg * 16 + g);
        half_step(0, g);
        if (g == 16 - SK) { wg_wait<1>(); mbar_arrive_warp(sb + BAR_EMPTY + ((g + 3) & 3) * 8); }
      }
      half_step(1, 16 - SK);
      half_step(1, 17 - SK);
      if (SK < 3 && wg == 0) nb_arrive(NB_ORDER_AB, 256);
      if (AREL && !wg) {
        if (SK > 1) { wg_wait<1>(); mbar_arrive_warp(sb + BAR_EMPTY + 2 * 8); }
        if (AREL == 1) { wg_wait<0>(); mbar_arrive_warp(sb + BAR_EMPTY + 3 * 8); }
      }
      mbar_wait(sb + BAR_IDX, 0);
      if (wg == 1) nb_sync(NB_STG, 256);
      wg_wait<(SK > 1 ? 2 : 1)>();
      PROF_C(wt == 0, 3 + wg * 8);

      const uint32_t st_row = (uint32_t)(w * 16 + (lane & 15)) * 128;
      uint32_t l2k[8 + PA];
#pragma unroll
      for (int u = 0; u < PA; u++) l2k[u] = 0x3FB8AA3Bu;
#pragma unroll
      for (int u = 0; u < 8; u++) {
        const int m = u >> 2, j = u & 3;
        const uint32_t a = sb + m * 8192 + st_row + ((((lane >> 4) + 2 * j) ^ (lane & 7)) << 4);
        const float* k = &acc[m][32 + 8 * j];
        const float l = __uint_as_float(l2k[u]);
        if (SK > 1 && u == M1) {
          wg_wait<1>();
          if (!AREL || wg) mbar_arrive_warp(sb + BAR_EMPTY + 2 * 8);
        }
        if (u == MM) {
          wg_wait<0>();
          if (AREL != 1 || wg) mbar_arrive_warp(sb + BAR_EMPTY + 3 * 8);
        }
        const float* v = &acc[m][64 + 8 * j];
        stsm4(a + OFF_V, pack2(v[0], v[1]), pack2(v[2], v[3]), pack2(v[4], v[5]), pack2(v[6], v[7]));
        const uint32_t r0 = phi2(k[0], k[1], l), r1 = phi2(k[2], k[3], l), r2 = phi2(k[4], k[5], l), r3 = phi2(k[6], k[7], l);
        stsm4(a + OFF_PK, r0, r1, r2, r3);
        if (u + PA < 8) l2k[u + PA] = lds32(sb + OFF_MISC + 20);
      }
      fence_async_smem();
      nb_sync(nb_self, 128);
      PROF_C(wt == 0, 8 + wg * 8);
      float c[36];
      const uint32_t dk = mkdesc(sb + OFF_PK, 16), dv = mkdesc(sb + OFF_V, OFF_ONES - OFF_V);
      wg_fence();
#pragma unroll
      for (int kk = 0; kk < 8; kk++) mma_ktv(c, dk + kk * 128, dv + (kk * 128 - (kk << 23)), kk ? 1 : 0);
      wg_commit();
      if (wg == 1) nb_arrive(NB_ORDER_BO, 256);
      auto reduce = [&](float4* dst, int gap) {
        wg_wait<0>();
        PROF_C(wt == 0, 4 + wg * 8);
        float u[18];
#pragma unroll
        for (int i = 0; i < 16; i++) u[i] = w >= 2 ? c[16 + i] : c[i];
#if NV == 6
        u[16] = c[32]; u[17] = c[34];
#pragma unroll
        for (int i = 0; i < 6; i++) {
          if (gap && i) __nanosleep(gap);
          red_add4(dst + i * 128, u[3 * i], u[3 * i + 1], u[3 * i + 2], 1.f);
        }
#else
        u[16] = __shfl_down_sync(~0u, u[15], 1);
        u[17] = lane & 2 ? c[34] : c[32];
#pragma unroll
        for (int i = 0; i < 5; i++) {
          if (gap && i) __nanosleep(gap);
          red_add4(dst + i * 128, u[3 * i], u[3 * i + 1], u[3 * i + 2], i < 3 && !(lane & 1) ? u[i == 0 ? 15 : i == 1 ? 17 : 16] : 1.f);
        }
#endif
      };
      const uint32_t zero = lds32(sb + OFF_ONES) & 1;
      float l2e = __uint_as_float(0x3FB8AA3Bu + zero);
      uint32_t dep = 0;
      float4 kv[NV];
#pragma unroll
      for (int u = 0; u < 8; u++) {
        if (u == KVE) {
          const float4* const kp = kvacc + (dep & zero);
          if (wg) {
#pragma unroll
            for (int i = 0; i < NV; i++) kv[i] = ld_relaxed_f4(kp + i * 128);
          }
          l2e = __uint_as_float(lds32(sb + OFF_MISC + 20));
        }
        if (u == PH) {
          if (PH) l2e = __uint_as_float(lds32(sb + OFF_MISC + 20 + (dep & zero)));
          if (wg) reduce(kvacc, 0);
          if (PH) l2e = __uint_as_float(lds32(sb + OFF_MISC + 20) | __float_as_uint(l2e));
          else l2e = __uint_as_float(lds32(sb + OFF_MISC + 20));
        }
#pragma unroll
        for (int i = 0; i < 4; i++) dep |= pq[u >> 2][u & 3][i] = phi2(acc[u >> 2][8 * (u & 3) + 2 * i], acc[u >> 2][8 * (u & 3) + 2 * i + 1], l2e);
      }
      float4* const kvp = kvacc + (dep & zero);
      if (!wg) reduce(kvp, RED_SLEEP);
      PROF_C(wt == 0 && kvp == kvacc, 34 + wg * 2);
      for (int tries = wg ? 0 : 9;; tries++) {
        if (tries > RETRY)
          while (ld_relaxed((const unsigned*)&(kvp - lane)[NV * 128 - 128 + 31].w) != 0x41800000u) __nanosleep(wg ? KV_SLEEP : KV_SLEEP_A);
        if (KVE == 8 || tries) {
#pragma unroll
          for (int i = 0; i < NV; i++) kv[i] = ld_relaxed_f4(kvp + i * 128);
        }
        const uint32_t kb = sb + OFF_KVB + (w >> 1) * 2560 + (w & 1) * 256;
        const uint32_t ka = kb + (lane >> 4) * 512 + (lane & 15) * 16;
        stsm4(ka, pack2(kv[0].x, kv[0].y), pack2(kv[0].z, kv[1].x), pack2(kv[1].y, kv[1].z), pack2(kv[2].x, kv[2].y));
#if NV == 6
        stsm4(ka + 1024, pack2(kv[2].z, kv[3].x), pack2(kv[3].y, kv[3].z), pack2(kv[4].x, kv[4].y), pack2(kv[4].z, kv[NV - 1].x));
        sts32(kb + 2048 + lane * 4, pack2(kv[NV - 1].y, kv[NV - 1].y));
        sts32(kb + 2048 + 128 + lane * 4, pack2(kv[NV - 1].z, kv[NV - 1].z));
        const bool ok = kv[0].w + kv[1].w + kv[2].w + kv[3].w + kv[4].w + kv[NV - 1].w == 96.f;
#else
        const uint32_t zz = pack2(kv[1].w, kv[1].w);
        if (!(lane & 1)) sts128(kb + 2048 + (lane & 2) * 64 + (lane >> 2) * 16, zz, zz, zz, zz);
        const float u15 = __shfl_up_sync(~0u, kv[2].w, 1);
        stsm4(ka + 1024, pack2(kv[2].z, kv[3].x), pack2(kv[3].y, kv[3].z), pack2(kv[4].x, kv[4].y), pack2(kv[4].z, lane & 1 ? u15 : kv[0].w));
        const bool ok = !(lane & 1) || kv[0].w + kv[1].w + kv[2].w + kv[3].w + kv[4].w == 80.f;
#endif
        if (__all_sync(~0u, ok)) { PROF_V(wg && lane == 0, 40 + w, tries * 100 + 2); break; }
      }
    }
    {
      PROF_C(wt == 0, 5 + wg * 8);
      fence_async_smem();
      nb_sync(nb_self, 128);
      float o[2][2][20];
      const uint32_t dz = mkdesc(sb + OFF_KVB, 128);
      wg_fence();
#pragma unroll
      for (int m = 0; m < 2; m++) {
#pragma unroll
        for (int h = 0; h < 2; h++)
#pragma unroll
          for (int kk = 0; kk < 2; kk++) mma_qkvz(o[m][h], pq[m][2 * h + kk], dz + (h * 160 + kk * 16), kk);
        wg_commit();
      }
      const uint32_t tmask = (lane & 3) == (lane >> 3), tbit = lds32(sb + OFF_MISC + 24) & tmask;
      float gr[2][2], sc[4];
#pragma unroll
      for (int i = 0; i < 4; i++) gr[i >> 1][i & 1] = __uint_as_float(lds32(sb + OFF_G + ((i >> 1) * 64 + (i & 1) * 8 + w * 16 + (lane >> 2)) * 4));
      if (wg == 1) {
        mbar_arrive_warp(sb + BAR_OST);
        mbar_wait(sb + BAR_OA, 0);
      }
      const uint32_t os = sb + (wg ? OFF_MOD : OFF_PK) + w * 2048;
      uint8_t* const og = (uint8_t*)gs->o[tm][wg * 8 + tn] + w * 2048;
#pragma unroll
      for (int m = 0; m < 2; m++) {
        if (m == 0) wg_wait<1>();
        if (m == 0) PROF_C(wt == 0, 6 + wg * 8);
#pragma unroll
        for (int h = 0; h < 2; h++) {
          const float* oo = o[m][h];
          uint32_t pin = 0;
          if (!m && h) {
            wg_wait<0>();
#pragma unroll
            for (int i = 0; i < 4; i++) pin |= __float_as_uint(sc[i] = gr[1][i & 1] * rcp(o[1][i >> 1][16 + (i & 1) * 2] + 1e-6f));
            pin &= __float_as_uint(gr[0][0]) & 16;
          }
          const float s0 = m ? sc[2 * h] : gr[m][0] * rcp(oo[16] + 1e-6f), s1 = m ? sc[2 * h + 1] : gr[m][1] * rcp(oo[18] + 1e-6f);
#pragma unroll
          for (int j = 0; j < 2; j++)
            stsm4(os + m * 8192 + (lane & 15) * 128 + ((((lane >> 4) + 4 * h + 2 * j) ^ (lane & 7)) << 4) + (j ? pin : 0),
                  (pack2(oo[8 * j] * s0, oo[8 * j + 1] * s0) & ~tmask) | tbit, (pack2(oo[8 * j + 2] * s1, oo[8 * j + 3] * s1) & ~tmask) | tbit,
                  pack2(oo[8 * j + 4] * s0, oo[8 * j + 5] * s0), pack2(oo[8 * j + 6] * s1, oo[8 * j + 7] * s1));
        }
        fence_async_smem();
        __syncwarp();
        if (OWNH && wg) mbar_arrive_warp(sb + (m ? BAR_OWN : BAR_OWN0));
        if (elect()) bulk_store(og + m * 8192, os + m * 8192, 2048);
      }
      if (elect()) {
        bulk_commit();
        if (!OWNH && wg) mbar_arrive(sb + BAR_OWN);
        PROF(wt == 0, 7 + wg * 8);
        if (AFLAG && !wg) red_add(gs->cnt[tm], 1u << tn * 4);
        asm volatile("cp.async.bulk.wait_group.read 0;" ::: "memory");
        PROF(wt == 0, 17 + wg);
        PROF(wt == 96, 38 + wg);
      }
    }

    __syncwarp();
    const uint32_t par = lds32(sb + OFF_MISC + 24), cw = lane * 32 + (lane & 4) * 4 + (lane >> 3) * 4;
    auto check_tile = [&](int g, uint32_t s) {
      const uint32_t a = sb + OFF_RING + s * O_BYTES + w * 2048, fix = sb + BAR_FIX + warp * 8;
      for (;;) {
        const uint32_t u0 = lds32(a + cw), u1 = lds32(a + cw + 1024), u2 = lds32(a + cw + 8192), u3 = lds32(a + cw + 9216);
        if (__all_sync(~0u, !(mism(mism(u0, u1, par), mism(u2, u3, par), 0) & 1))) break;
        PROF_V(lane == 0, 44 + g, 102);
        const int slab = g < OWN ? g : g < PEER ? g - 1 : g == PEER ? 8 + (tn ^ 1) : g - 10 < (tn & 6) ? g - 2 : g;
        const uint4* src = gs->o[tm][slab] + w * 128;
        const uint32_t ph = !mbar_test(fix, 1);
        fence_async_smem();
        __syncwarp();
        if (elect()) { mbar_expect_tx(fix, 4096); bulk_load(a, src, 2048, fix); bulk_load(a + 8192, src + 512, 2048, fix); }
        mbar_wait(fix, ph);
      }
    };
    if (wg == 1) {
#pragma unroll 1
      for (int g = 10; g < 16; g++) {
        const uint32_t s = g == 15 ? 0 : g - 10;
        mbar_wait(sb + BAR_LAND + (g - 10) * 8, 0);
        PROF_C(wt == 0, 214 + g);
        check_tile(g, s);
        if (w) nb_arrive(NB_CHK + (g & 1), 128);
        else { nb_sync(NB_CHK + (g & 1), 128); mbar_arrive_warp(sb + BAR_FULL + s * 8); }
        if (g & 1) nb_sync(nb_self, 128);
      }
    } else {
      nb_arrive(NB_STG, 256);
      float acc[2][64];
      mbar_wait(sb + BAR_W31, 0);
#pragma unroll 1
      for (int g = 0; g < PC; g++) { mbar_wait(sb + BAR_EMPTY + g * 8, 1); mbar_wait(sb + BAR_FULL + g * 8, 0); check_tile(g, g); }
      nb_sync(NB_ORDER_BO, 256);
      PROF_C(wt == 0, 26);
      uint32_t xr[2][8][4], q[2][2];
      const uint32_t ta = sb + OFF_PK + (uint32_t)(w * 16 + (lane & 15)) * 128;
      auto o_step = [&](int g) {
        const uint32_t r = g * 52 >> 8, s = g - r * 5;
        const uint32_t da = da0 + s * (O_BYTES >> 4), db = db0 + s * (O_BYTES >> 4);
        mbar_wait(sb + BAR_FULL + s * 8, r & 1);
        if (g >= PC) check_tile(g, s);
        PROF_C(wt == 0, 96 + g);
        wg_fence();
#pragma unroll
        for (int kk = 0; kk < 4; kk++)
#pragma unroll
          for (int m = 0; m < 2; m++) mma_out(acc[m], da + (m * 512 + kk * 2), db + kk * 128, kk ? 1 : g);
        wg_commit();
        wg_wait<1>();
        if (g) mbar_arrive_warp(sb + BAR_EMPTY + (s ? s - 1 : 4) * 8);
      };
#pragma unroll 1
      for (int g = 0; g < 13 - TL; g++) {
        const uint32_t r = g * 52 >> 8, s = g - r * 5;
        const uint32_t da = da0 + (g == OWN ? 5 : s) * (O_BYTES >> 4), db = db0 + s * (O_BYTES >> 4);
        if (g == OWN) {
          wg_wait<0>();
          mbar_arrive_warp(sb + BAR_EMPTY + (OWN + 4) % 5 * 8);
          mbar_wait(sb + BAR_OWN, 0);
        }
        mbar_wait(sb + BAR_FULL + s * 8, r & 1);
        if (g != OWN && g >= PC) check_tile(g, s);
        PROF_C(wt == 0, 96 + g);
        wg_fence();
#pragma unroll
        for (int kk = 0; kk < 4; kk++)
#pragma unroll
          for (int m = 0; m < 2; m++) mma_out(acc[m], da + (m * 512 + kk * 2), db + kk * 128, kk ? 1 : g);
        wg_commit();
        wg_wait<1>();
        if (~(1 | 1 << OWN) >> g & 1) mbar_arrive_warp(sb + BAR_EMPTY + (s ? s - 1 : 4) * 8);
      }
      mbar_wait(sb + BAR_X, 0);
      if (((0xFFFF - (lds32(sb + OFF_MISC + 16) & 0xFFFF)) >> 7) == tm) mbar_wait(sb + BAR_Y, 0);
#pragma unroll
      for (int u = 0; u < 4; u++) {
        const int m = u >> 1, g = 13 - TL + u;
        const float g1 = 1.f - __uint_as_float(lds32(sb + OFF_G + (m * 64 + w * 16 + (u & 1) * 8 + (lane >> 2)) * 4));
        q[m][u & 1] = pack2(g1, g1);
#pragma unroll
        for (int j = 0; j < 4; j++) ldsm4(ta + (u & 1) * 16384 + m * 8192 + ((((lane >> 4) + 2 * j) ^ (lane & 7)) << 4), xr[m][(u & 1) * 4 + j]);
        if (u == 3) break;
        mbar_wait(sb + BAR_FULL + g % 5 * 8, g / 5 & 1);
        PROF_C(wt == 0, 96 + g);
        wg_fence();
#pragma unroll
        for (int kk = 0; kk < 4; kk++)
#pragma unroll
          for (int mm = 0; mm < 2; mm++)
            mma_out(acc[mm], da0 + (g % 5 * (O_BYTES >> 4) + mm * 512 + kk * 2), db0 + (g % 5 * (O_BYTES >> 4) + kk * 128), 1);
        wg_commit();
        wg_wait<1>();
        if (g <= 11) mbar_arrive_warp(sb + BAR_EMPTY + (g + 4) % 5 * 8);
      }
#pragma unroll
      for (int m = 0; m < 2; m++) {
#pragma unroll
        for (int g = 16 - TL; g < 16; g++) {
          if (m == 0) { mbar_wait(sb + BAR_FULL + g % 5 * 8, g / 5 & 1); PROF_C(wt == 0, 96 + g); wg_fence(); }
#pragma unroll
          for (int kk = 0; kk < 4; kk++)
            mma_out(acc[m], da0 + (g % 5 * (O_BYTES >> 4) + m * 512 + kk * 2), db0 + (g % 5 * (O_BYTES >> 4) + kk * 128), 1);
        }
        wg_commit();
      }
      mbar_arrive_warp(sb + BAR_DONE);
#pragma unroll
      for (int m = 0; m < 2; m++) {
        if (m == 0) wg_wait<1>(); else wg_wait<0>();
        if (m) PROF(wt == 0, 31);
#pragma unroll
        for (int h = 0; h < 2; h++) {
#pragma unroll
          for (int j = 4 * h; j < 4 * h + 4; j++) {
            const float* v = &acc[m][8 * j];
            stsm4(ta + h * 16384 + m * 8192 + ((((lane >> 4) + 2 * (j & 3)) ^ (lane & 7)) << 4),
                  fma_bf2(xr[m][j][0], q[m][0], pack2(v[0], v[1])), fma_bf2(xr[m][j][1], q[m][1], pack2(v[2], v[3])),
                  fma_bf2(xr[m][j][2], q[m][0], pack2(v[4], v[5])), fma_bf2(xr[m][j][3], q[m][1], pack2(v[6], v[7])));
          }
          fence_async_smem();
          __syncwarp();
          if (elect()) tma2d_store(&p.out, sb + OFF_PK + h * 16384 + m * 8192 + w * 2048, tn * 128 + h * 64, tm * 128 + m * 64 + w * 16);
          if (m && h && elect()) { bulk_commit(); asm volatile("cp.async.bulk.wait_group.read 0;" ::: "memory"); }
        }
        if (!m) PROF(wt == 0, 33);
      }
      PROF(wt == 0, 32);
    }
  }
}

typedef CUresult (*EncodeFn)(CUtensorMap*, CUtensorMapDataType, cuuint32_t, void*, const cuuint64_t*, const cuuint64_t*, const cuuint32_t*,
                             const cuuint32_t*, CUtensorMapInterleave, CUtensorMapSwizzle, CUtensorMapL2promotion, CUtensorMapFloatOOBfill);

void encode(EncodeFn fn, CUtensorMap* m, const void* ptr, int rank, const cuuint64_t* dims, const cuuint64_t* strides, const cuuint32_t* box,
            CUtensorMapSwizzle sw, CUtensorMapDataType dt = CU_TENSOR_MAP_DATA_TYPE_BFLOAT16, CUtensorMapL2promotion pr = CU_TENSOR_MAP_L2_PROMOTION_L2_128B) {
  const cuuint32_t es[3] = {1, 1, 1};
  fn(m, dt, rank, const_cast<void*>(ptr), dims, strides, box, es, CU_TENSOR_MAP_INTERLEAVE_NONE, sw,
     pr, CU_TENSOR_MAP_FLOAT_OOB_FILL_NONE);
}

}

extern "C" void kernel_launch(void* const* d_in, const int* in_sizes, int n_in, void* d_out, int out_size) {
  (void)in_sizes; (void)n_in; (void)out_size;
  EncodeFn fn = nullptr;
  cudaDriverEntryPointQueryResult qr;
  cudaGetDriverEntryPoint("cuTensorMapEncodeTiled", (void**)&fn, cudaEnableDefault, &qr);

  Params p;
  {
    const cuuint64_t dims[2] = {D_, S_}, str[1] = {D_ * 2};
    const cuuint32_t box[2] = {64, 128}, box_st[2] = {64, 16}, box_r[2] = {256, 16};
    encode(fn, &p.xr, d_in[0], 2, dims, str, box_r, CU_TENSOR_MAP_SWIZZLE_NONE);
#define XPROMO CU_TENSOR_MAP_L2_PROMOTION_L2_128B
    encode(fn, &p.x, d_in[0], 2, dims, str, box, CU_TENSOR_MAP_SWIZZLE_128B, CU_TENSOR_MAP_DATA_TYPE_BFLOAT16, XPROMO);
    encode(fn, &p.out, d_out, 2, dims, str, box_st, CU_TENSOR_MAP_SWIZZLE_128B);
  }
  {
    const cuuint64_t dims[3] = {D_, D_, 3}, str[2] = {3 * D_ * 2, D_ * 2};
    const cuuint32_t box[3] = {64, 64, 3};
    encode(fn, &p.w, d_in[1], 3, dims, str, box, CU_TENSOR_MAP_SWIZZLE_128B);
  }
  {
    const cuuint64_t dims[3] = {64, D_, D_ / 64}, str[2] = {D_ * 2, 128};
    const cuuint32_t box[3] = {64, 64, 2};
    encode(fn, &p.wo, d_in[2], 3, dims, str, box, CU_TENSOR_MAP_SWIZZLE_128B);
  }
  {
    const cuuint64_t dims[3] = {F_, D_ / 4, 4}, str[2] = {F_ * 8, F_ * 2};
    const cuuint32_t box[3] = {32, 16, 4};
    encode(fn, &p.gate, d_in[5], 3, dims, str, box, CU_TENSOR_MAP_SWIZZLE_NONE);
    encode(fn, &p.up, d_in[6], 3, dims, str, box, CU_TENSOR_MAP_SWIZZLE_NONE);
  }
  {
    const cuuint64_t dims[3] = {D_ / 4, F_, 2}, str[2] = {D_ * 2, D_};
    const cuuint32_t box[3] = {256, 4, 2};
    encode(fn, &p.down, d_in[7], 3, dims, str, box, CU_TENSOR_MAP_SWIZZLE_NONE, CU_TENSOR_MAP_DATA_TYPE_UINT32);
  }
  void* gs = nullptr;
  cudaGetSymbolAddress(&gs, g_scratch);
  typedef const __nv_bfloat16* bp;
  int dev = 0, sms = 0;
  cudaGetDevice(&dev);
  cudaDeviceGetAttribute(&sms, cudaDevAttrMultiProcessorCount, dev);
  const bool by_sm = BYSM && sms == NGRID;
  const auto kernel = by_sm ? fused_kernel<true> : fused_kernel<false>;
  cudaFuncSetAttribute(kernel, cudaFuncAttributeMaxDynamicSharedMemorySize, SMEM_BYTES);
  kernel<<<by_sm ? NGRID : NCTA, NTHREADS, SMEM_BYTES, cudaStreamPerThread>>>((bp)d_in[0], (Scratch*)gs, (bp)d_in[5], (bp)d_in[6], (bp)d_in[4], (bp)d_in[8], p);
}
```

```cpp
#include <cuda_runtime.h>
#include <cuda.h>
#include <cuda_bf16.h>
#include <stdint.h>
#include <stddef.h>

namespace {

constexpr int S_ = 2048, D_ = 1024, F_ = 3584;
constexpr int NCTA = 128, NGRID = 132, NTHREADS = 512;
constexpr int MOD_CTAS = F_ / 32;

#define PC 2
#define PRE 2
#define ST1 700
#define RT_G0 2
#define RT_ROT 2
#define RT_SLEEP 500
#define PF_MOD 6
#define MOD_START 9
#define MM 4
#define PA 4
#define RED_SLEEP 32
#define RETRY 1
#define KV_SLEEP_A 128
#define KV_SLEEP 50
#define OWN 5
#define TL 3
#define MAP 1
#define NOMOD 5
#define FIXR 2
#define PH 0
#define KVE 8
#define MX 1
#define FENCES 0
#define FSL 128
#define AFLAG 1
#define AW 1
#define SK 2
#define AREL 0
#define M0 1
#define ST2 (2 * ST1)
#define ST3 (3 * ST1)
#define ILV 0
#define TQ 3
#define STQ ""
#define M1 1
#define PAIRED 1
#define BYSM 1

constexpr uint32_t A_BYTES = 16384, BQ_BYTES = 24576, BO_BYTES = 16384, STAGE_BYTES = A_BYTES + BQ_BYTES, O_BYTES = A_BYTES + BO_BYTES;
constexpr int MOD_BUFS = 3, MOD_BUFS0 = MOD_BUFS + MX;
static_assert(MOD_START + MOD_BUFS0 <= 16, "first FFN round is requested during wave A");
constexpr uint32_t OFF_RING = 0;
constexpr uint32_t OFF_MOD = 4 * STAGE_BYTES;
constexpr uint32_t OFF_PK = OFF_MOD + MOD_BUFS * 8192;
constexpr uint32_t OFF_V = OFF_PK + 16384;
constexpr uint32_t OFF_ONES = OFF_V + 16384;
constexpr uint32_t OFF_KVB = OFF_ONES + 2048;
constexpr uint32_t OFF_XSEL = OFF_KVB + 5120;
constexpr uint32_t OFF_G = OFF_XSEL + 2048;
constexpr uint32_t OFF_PART = OFF_G + 512;
constexpr uint32_t OFF_MISC = OFF_PART + 576;
constexpr uint32_t OFF_BAR = OFF_MISC + 32;
constexpr uint32_t BAR_FULL = OFF_BAR, BAR_EMPTY = OFF_BAR + 40, BAR_RTD = OFF_BAR + 80, BAR_Y = OFF_BAR + 88, BAR_DONE = OFF_BAR + 96,
                   BAR_X = OFF_BAR + 104, BAR_OA = OFF_BAR + 112, BAR_OWN = OFF_BAR + 120, BAR_OST = OFF_BAR + 128, BAR_PA = OFF_BAR + 136,
                   BAR_W31 = OFF_BAR + 144, BAR_MFULL = OFF_BAR + 152, BAR_MEMPTY = BAR_MFULL + MOD_BUFS0 * 8,
                   BAR_IDX = BAR_MEMPTY + MOD_BUFS * 8,
                   BAR_OWN0 = BAR_IDX + 8;
constexpr uint32_t SMEM_BYTES = OFF_BAR + 384;
static_assert(SMEM_BYTES <= 232448, "smem");

constexpr uint32_t BAR_LAND = OFF_BAR + 256, BAR_FIX = BAR_LAND + 64;
constexpr uint32_t BAR_RT = BAR_FIX;
static_assert(TL == 3 && PRE == 2 && BAR_OWN0 - OFF_BAR < 256, "warp w initialises barriers 2w and 2w + 1");
constexpr __host__ __device__ uint64_t bar_counts(int first) {
  uint64_t r = 0;
  for (uint32_t i = 0; i < 16; i++) {
    const uint32_t b = OFF_BAR + (first + i) * 8;
    const uint64_t c = b < BAR_EMPTY ? 2 : b == BAR_IDX ? 5 : b == BAR_Y || b == BAR_X || (b >= BAR_PA && b < BAR_MEMPTY) ? 1 : 4;
    r |= c << i * 4;
  }
  return r;
}

constexpr int NB_WG0 = 1, NB_ORDER_AB = 3, NB_ORDER_BO = 4, NB_STG = 5, NB_MODW = 6, NB_KEY = 7, NB_CHK = 8;

#ifndef NV
#define NV 5
#endif
constexpr int NCLR = NV * 4 + 5;
struct Scratch {
  float4 kv[2][8][NV][128];
  float y[8][D_];
  unsigned cnt[64][32];
  unsigned gslot[S_];
  unsigned rslot[8][NCTA];
  unsigned spare[128];
  unsigned block[NCTA];
  uint4 o[16][16][1024];
};
static_assert(offsetof(Scratch, gslot) == NCTA * NCLR * 64, "clear size");
__device__ __align__(1024) Scratch g_scratch;

#define PROF(cond, i) do {} while (0)
#define PROF_C(cond, i) do {} while (0)
#define PROF_P(cond, i) do {} while (0)
#define PROF_V(cond, i, v) do {} while (0)

__device__ __forceinline__ void mbar_init(uint32_t bar, int cnt) { asm volatile("mbarrier.init.shared::cta.b64 [%0], %1;" ::"r"(bar), "r"(cnt)); }
__device__ __forceinline__ void mbar_expect_tx(uint32_t bar, uint32_t bytes) { asm volatile("mbarrier.arrive.expect_tx.shared::cta.b64 _, [%0], %1;" ::"r"(bar), "r"(bytes) : "memory"); }
__device__ __forceinline__ void mbar_arrive(uint32_t bar) { asm volatile("mbarrier.arrive.shared::cta.b64 _, [%0];" ::"r"(bar) : "memory"); }
__device__ __forceinline__ uint32_t peer_addr(uint32_t a) {
  uint32_t r;
  asm volatile("{\n.reg .u32 c;\nmov.u32 c, %%cluster_ctarank;\nxor.b32 c, c, 1;\nmapa.shared::cluster.u32 %0, %1, c;\n}" : "=r"(r) : "r"(a));
  return r;
}
__device__ __forceinline__ void mbar_arrive_peer(uint32_t bar) { asm volatile("mbarrier.arrive.shared::cluster.b64 _, [%0];" ::"r"(bar) : "memory"); }
__device__ __forceinline__ uint32_t mism(uint32_t a, uint32_t b, uint32_t p) {
  uint32_t r; asm("lop3.b32 %0, %1, %2, %3, 0x7E;" : "=r"(r) : "r"(a), "r"(b), "r"(p)); return r;
}
__device__ __forceinline__ bool elect() {
  uint32_t r;
  asm volatile("{\n.reg .pred p;\nelect.sync _|p, 0xffffffff;\nselp.u32 %0, 1, 0, p;\n}" : "=r"(r));
  return r;
}
__device__ __forceinline__ uint32_t fresh_tid() { uint32_t r; asm volatile("mov.u32 %0, %%tid.x;" : "=r"(r)); return r; }
__device__ __forceinline__ void mbar_arrive_warp(uint32_t bar) {
  asm volatile("{\n.reg .pred p;\nelect.sync _|p, 0xffffffff;\n@p mbarrier.arrive.shared::cta.b64 _, [%0];\n}" ::"r"(bar) : "memory");
}
__device__ __forceinline__ void mbar_wait(uint32_t bar, uint32_t parity) {
  asm volatile("{\n.reg .pred p;\nWAIT_L:\nmbarrier.try_wait.parity.shared::cta.b64 p, [%0], %1;\n@p bra DONE_L;\nbra WAIT_L;\nDONE_L:\n}"
               ::"r"(bar), "r"(parity) : "memory");
}
__device__ __forceinline__ uint32_t mbar_test(uint32_t bar, uint32_t parity) {
  uint32_t ok;
  asm volatile("{\n.reg .pred p;\nmbarrier.test_wait.parity.shared::cta.b64 p, [%1], %2;\nselp.u32 %0, 1, 0, p;\n}" : "=r"(ok) : "r"(bar), "r"(parity) : "memory");
  return ok;
}
constexpr unsigned long long WATCHDOG_NS = 2000000000ull;
__device__ __forceinline__ unsigned long long gtime() { unsigned long long t; asm volatile("mov.u64 %0, %%globaltimer;" : "=l"(t)); return t; }
__device__ __forceinline__ uint32_t clock32() { uint32_t t; asm volatile("mov.u32 %0, %%clock;" : "=r"(t)); return t; }
__device__ __forceinline__ void mbar_wait_bounded(uint32_t bar, uint32_t parity) {
  unsigned long long t0 = 0;
  for (;;) {
    uint32_t ok;
    asm volatile("{\n.reg .pred p;\nmbarrier.try_wait.parity.shared::cta.b64 p, [%1], %2;\nselp.u32 %0, 1, 0, p;\n}" : "=r"(ok) : "r"(bar), "r"(parity) : "memory");
    if (ok) break;
    const unsigned long long t1 = gtime();
    if (t0 == 0) t0 = t1;
    if (t1 - t0 > WATCHDOG_NS) __trap();
  }
}
__device__ __forceinline__ void tma2d(uint32_t dst, const CUtensorMap* m, int c0, int c1, uint32_t bar) {
  asm volatile("cp.async.bulk.tensor.2d.shared::cluster.global.mbarrier::complete_tx::bytes [%0], [%1, {%3, %4}], [%2];"
               ::"r"(dst), "l"(m), "r"(bar), "r"(c0), "r"(c1) : "memory");
}
__device__ __forceinline__ void tma3d(uint32_t dst, const CUtensorMap* m, int c0, int c1, int c2, uint32_t bar) {
  asm volatile("cp.async.bulk.tensor.3d.shared::cluster.global.mbarrier::complete_tx::bytes [%0], [%1, {%3, %4, %5}], [%2];"
               ::"r"(dst), "l"(m), "r"(bar), "r"(c0), "r"(c1), "r"(c2) : "memory");
}
__device__ __forceinline__ void bulk_load(uint32_t dst, const void* src, uint32_t bytes, uint32_t bar) {
  asm volatile("cp.async.bulk.shared::cluster.global.mbarrier::complete_tx::bytes [%0], [%1], %2, [%3];" ::"r"(dst), "l"(src), "r"(bytes), "r"(bar) : "memory");
}
__device__ __forceinline__ void bulk_store(void* dst, uint32_t src, uint32_t bytes) {
  asm volatile("cp.async.bulk.global.shared::cta.bulk_group [%0], [%1], %2;" ::"l"(dst), "r"(src), "r"(bytes) : "memory");
}
__device__ __forceinline__ void bulk_push(uint32_t dst, uint32_t src, uint32_t bytes, uint32_t bar) {
  asm volatile("cp.async.bulk.shared::cluster.shared::cta.mbarrier::complete_tx::bytes [%0], [%1], %2, [%3];" ::"r"(dst), "r"(src), "r"(bytes), "r"(bar) : "memory");
}
__device__ __forceinline__ void bulk_commit() { asm volatile("cp.async.bulk.commit_group;" ::: "memory"); }
__device__ __forceinline__ void bulk_prefetch(const void* p, uint32_t bytes) {
  asm volatile("cp.async.bulk.prefetch.L2.global [%0], %1;" ::"l"(p), "r"(bytes) : "memory");
}
__device__ __forceinline__ void tma2d_store(const CUtensorMap* m, uint32_t src, int c0, int c1) {
  asm volatile("cp.async.bulk.tensor.2d.global.shared::cta.bulk_group [%0, {%2, %3}], [%1];" ::"l"(m), "r"(src), "r"(c0), "r"(c1) : "memory");
}
__device__ __forceinline__ void wg_fence() { asm volatile("wgmma.fence.sync.aligned;" ::: "memory"); }
__device__ __forceinline__ void wg_commit() { asm volatile("wgmma.commit_group.sync.aligned;" ::: "memory"); }
template <int N> __device__ __forceinline__ void wg_wait() { asm volatile("wgmma.wait_group.sync.aligned %0;" ::"n"(N) : "memory"); }
__device__ __forceinline__ void fence_async_smem() { asm volatile("fence.proxy.async.shared::cta;" ::: "memory"); }
__device__ __forceinline__ void fence_async_global() { asm volatile("fence.proxy.async.global;" ::: "memory"); }
__device__ __forceinline__ void fence_release() { asm volatile("fence.release.gpu;" ::: "memory"); }
__device__ __forceinline__ void fence_acquire() { asm volatile("fence.acquire.gpu;" ::: "memory"); }
__device__ __forceinline__ void nb_sync(int id, int n) { asm volatile("bar.sync %0, %1;" ::"r"(id), "r"(n) : "memory"); }
__device__ __forceinline__ void nb_arrive(int id, int n) { asm volatile("bar.arrive %0, %1;" ::"r"(id), "r"(n) : "memory"); }
__device__ __forceinline__ void stsm4(uint32_t addr, uint32_t r0, uint32_t r1, uint32_t r2, uint32_t r3) {
  asm volatile("stmatrix.sync.aligned.m8n8.x4.shared.b16 [%0], {%1, %2, %3, %4};" ::"r"(addr), "r"(r0), "r"(r1), "r"(r2), "r"(r3) : "memory");
}
__device__ __forceinline__ void sts128(uint32_t addr, uint32_t a, uint32_t b, uint32_t c, uint32_t d) {
  asm volatile("st.shared.v4.b32 [%0], {%1, %2, %3, %4};" ::"r"(addr), "r"(a), "r"(b), "r"(c), "r"(d) : "memory");
}
__device__ __forceinline__ uint32_t pack2(float lo, float hi) {
  uint32_t r; asm("cvt.rn.bf16x2.f32 %0, %1, %2;" : "=r"(r) : "f"(hi), "f"(lo)); return r;
}
__device__ __forceinline__ float bf_lo(uint32_t v) { return __uint_as_float(v << 16); }
__device__ __forceinline__ float bf_hi(uint32_t v) { return __uint_as_float(v & 0xffff0000u); }
__device__ __forceinline__ float bf_round(float v) { return __bfloat162float(__float2bfloat16_rn(v)); }
__device__ __forceinline__ void ldsm4(uint32_t addr, uint32_t (&r)[4]) {
  asm volatile("ldmatrix.sync.aligned.m8n8.x4.shared.b16 {%0, %1, %2, %3}, [%4];" : "=r"(r[0]), "=r"(r[1]), "=r"(r[2]), "=r"(r[3]) : "r"(addr) : "memory");
}
__device__ __forceinline__ uint4 lds128(uint32_t addr) {
  uint4 v; asm volatile("ld.volatile.shared.v4.u32 {%0, %1, %2, %3}, [%4];" : "=r"(v.x), "=r"(v.y), "=r"(v.z), "=r"(v.w) : "r"(addr) : "memory"); return v;
}
__device__ __forceinline__ uint2 lds64(uint32_t addr) { uint2 v; asm volatile("ld.volatile.shared.v2.u32 {%0, %1}, [%2];" : "=r"(v.x), "=r"(v.y) : "r"(addr) : "memory"); return v; }
__device__ __forceinline__ uint32_t lds32(uint32_t addr) { uint32_t v; asm volatile("ld.volatile.shared.u32 %0, [%1];" : "=r"(v) : "r"(addr) : "memory"); return v; }
__device__ __forceinline__ void sts32(uint32_t addr, uint32_t v) { asm volatile("st.shared.u32 [%0], %1;" ::"r"(addr), "r"(v) : "memory"); }
__device__ __forceinline__ uint32_t fma_bf2(uint32_t a, uint32_t b, uint32_t c) { uint32_t r; asm("fma.rn.bf16x2 %0, %1, %2, %3;" : "=r"(r) : "r"(a), "r"(b), "r"(c)); return r; }
__device__ __forceinline__ unsigned ld_relaxed(const unsigned* p) { unsigned v; asm volatile("ld.relaxed.gpu.global.u32 %0, [%1];" : "=r"(v) : "l"(p) : "memory"); return v; }
__device__ __forceinline__ void st_relaxed(unsigned* p, unsigned v) { asm volatile("st.relaxed.gpu.global.u32 [%0], %1;" ::"l"(p), "r"(v) : "memory"); }
__device__ __forceinline__ uint4 ld_relaxed4(const void* p) {
  uint4 v; asm volatile("ld.relaxed.gpu.global.v4.u32 {%0, %1, %2, %3}, [%4];" : "=r"(v.x), "=r"(v.y), "=r"(v.z), "=r"(v.w) : "l"(p) : "memory"); return v;
}
__device__ __forceinline__ float4 ld_relaxed_f4(const void* p) {
  float4 v; asm volatile("ld.relaxed.gpu.global.v4.f32 {%0, %1, %2, %3}, [%4];" : "=f"(v.x), "=f"(v.y), "=f"(v.z), "=f"(v.w) : "l"(p) : "memory"); return v;
}
__device__ __forceinline__ void red_add4(void* p, float a, float b, float c, float d) {
  asm volatile("red.relaxed.gpu.global.add.v4.f32 [%0], {%1, %2, %3, %4};" ::"l"(p), "f"(a), "f"(b), "f"(c), "f"(d) : "memory");
}
__device__ __forceinline__ void red_add(unsigned* p, unsigned v) { asm volatile("red.relaxed.gpu.global.add.u32 [%0], %1;" ::"l"(p), "r"(v) : "memory"); }
__device__ __forceinline__ void wait_counter(const unsigned* p, unsigned target) {
  while (ld_relaxed(p) < target) __nanosleep(32);
  fence_acquire();
}
__device__ __forceinline__ float rcp(float v) { float r; asm("rcp.approx.ftz.f32 %0, %1;" : "=f"(r) : "f"(v)); return r; }
__device__ __forceinline__ float sigmoidf_(float v) { return rcp(1.f + __expf(-v)); }
__device__ __forceinline__ uint32_t phi2(float a, float b, float l2e = 1.4426950408889634f) {
  float ea, eb;
  asm("ex2.approx.ftz.f32 %0, %1;" : "=f"(ea) : "f"(a * l2e));
  asm("ex2.approx.ftz.f32 %0, %1;" : "=f"(eb) : "f"(b * l2e));
  uint32_t t = pack2(a, b), e = pack2(ea, eb), r;
  asm("max.NaN.bf16x2 %0, %0, %1;" : "+r"(t) : "r"(0x35863586u));
  asm("min.bf16x2 %0, %0, %1;" : "+r"(e) : "r"(0x3F803F80u));
  asm("add.rn.bf16x2 %0, %1, %2;" : "=r"(r) : "r"(t), "r"(e));
  return r;
}
__device__ __forceinline__ uint32_t mkdesc(uint32_t addr, uint32_t lbo) { return ((addr & 0x3FFFF) >> 4) | ((lbo >> 4) << 16); }

__device__ __forceinline__ void mma_qkv(float (&d)[96], uint32_t da, uint32_t db, int sc) {
  asm volatile("{\n.reg .pred p;\n.reg .b64 da, db;\nmov.b64 da, {%96, 0x40000040};\nmov.b64 db, {%97, 0x40000040};\nsetp.ne.b32 p, %98, 0;\n"
    "wgmma.mma_async.sync.aligned.m64n192k16.f32.bf16.bf16 "
    "{%0,%1,%2,%3,%4,%5,%6,%7,%8,%9,%10,%11,%12,%13,%14,%15,%16,%17,%18,%19,%20,%21,%22,%23,"
    "%24,%25,%26,%27,%28,%29,%30,%31,%32,%33,%34,%35,%36,%37,%38,%39,%40,%41,%42,%43,%44,%45,%46,%47,"
    "%48,%49,%50,%51,%52,%53,%54,%55,%56,%57,%58,%59,%60,%61,%62,%63,%64,%65,%66,%67,%68,%69,%70,%71,"
    "%72,%73,%74,%75,%76,%77,%78,%79,%80,%81,%82,%83,%84,%85,%86,%87,%88,%89,%90,%91,%92,%93,%94,%95}, "
    "da, db, p, 1, 1, 0, 1;\n}\n"
    : "+f"(d[0]), "+f"(d[1]), "+f"(d[2]), "+f"(d[3]), "+f"(d[4]), "+f"(d[5]), "+f"(d[6]), "+f"(d[7]),
      "+f"(d[8]), "+f"(d[9]), "+f"(d[10]), "+f"(d[11]), "+f"(d[12]), "+f"(d[13]), "+f"(d[14]), "+f"(d[15]),
      "+f"(d[16]), "+f"(d[17]), "+f"(d[18]), "+f"(d[19]), "+f"(d[20]), "+f"(d[21]), "+f"(d[22]), "+f"(d[23]),
      "+f"(d[24]), "+f"(d[25]), "+f"(d[26]), "+f"(d[27]), "+f"(d[28]), "+f"(d[29]), "+f"(d[30]), "+f"(d[31]),
      "+f"(d[32]), "+f"(d[33]), "+f"(d[34]), "+f"(d[35]), "+f"(d[36]), "+f"(d[37]), "+f"(d[38]), "+f"(d[39]),
      "+f"(d[40]), "+f"(d[41]), "+f"(d[42]), "+f"(d[43]), "+f"(d[44]), "+f"(d[45]), "+f"(d[46]), "+f"(d[47]),
      "+f"(d[48]), "+f"(d[49]), "+f"(d[50]), "+f"(d[51]), "+f"(d[52]), "+f"(d[53]), "+f"(d[54]), "+f"(d[55]),
      "+f"(d[56]), "+f"(d[57]), "+f"(d[58]), "+f"(d[59]), "+f"(d[60]), "+f"(d[61]), "+f"(d[62]), "+f"(d[63]),
      "+f"(d[64]), "+f"(d[65]), "+f"(d[66]), "+f"(d[67]), "+f"(d[68]), "+f"(d[69]), "+f"(d[70]), "+f"(d[71]),
      "+f"(d[72]), "+f"(d[73]), "+f"(d[74]), "+f"(d[75]), "+f"(d[76]), "+f"(d[77]), "+f"(d[78]), "+f"(d[79]),
      "+f"(d[80]), "+f"(d[81]), "+f"(d[82]), "+f"(d[83]), "+f"(d[84]), "+f"(d[85]), "+f"(d[86]), "+f"(d[87]),
      "+f"(d[88]), "+f"(d[89]), "+f"(d[90]), "+f"(d[91]), "+f"(d[92]), "+f"(d[93]), "+f"(d[94]), "+f"(d[95])
    : "r"(da), "r"(db), "r"(sc));
}

__device__ __forceinline__ void mma_out(float (&d)[64], uint32_t da, uint32_t db, int sc) {
  asm volatile("{\n.reg .pred p;\n.reg .b64 da, db;\nmov.b64 da, {%64, 0x40000040};\nmov.b64 db, {%65, 0x40000040};\nsetp.ne.b32 p, %66, 0;\n"
    "wgmma.mma_async.sync.aligned.m64n128k16.f32.bf16.bf16 "
    "{%0,%1,%2,%3,%4,%5,%6,%7,%8,%9,%10,%11,%12,%13,%14,%15,%16,%17,%18,%19,%20,%21,%22,%23,"
    "%24,%25,%26,%27,%28,%29,%30,%31,%32,%33,%34,%35,%36,%37,%38,%39,%40,%41,%42,%43,%44,%45,%46,%47,"
    "%48,%49,%50,%51,%52,%53,%54,%55,%56,%57,%58,%59,%60,%61,%62,%63}, "
    "da, db, p, 1, 1, 0, 1;\n}\n"
    : "+f"(d[0]), "+f"(d[1]), "+f"(d[2]), "+f"(d[3]), "+f"(d[4]), "+f"(d[5]), "+f"(d[6]), "+f"(d[7]),
      "+f"(d[8]), "+f"(d[9]), "+f"(d[10]), "+f"(d[11]), "+f"(d[12]), "+f"(d[13]), "+f"(d[14]), "+f"(d[15]),
      "+f"(d[16]), "+f"(d[17]), "+f"(d[18]), "+f"(d[19]), "+f"(d[20]), "+f"(d[21]), "+f"(d[22]), "+f"(d[23]),
      "+f"(d[24]), "+f"(d[25]), "+f"(d[26]), "+f"(d[27]), "+f"(d[28]), "+f"(d[29]), "+f"(d[30]), "+f"(d[31]),
      "+f"(d[32]), "+f"(d[33]), "+f"(d[34]), "+f"(d[35]), "+f"(d[36]), "+f"(d[37]), "+f"(d[38]), "+f"(d[39]),
      "+f"(d[40]), "+f"(d[41]), "+f"(d[42]), "+f"(d[43]), "+f"(d[44]), "+f"(d[45]), "+f"(d[46]), "+f"(d[47]),
      "+f"(d[48]), "+f"(d[49]), "+f"(d[50]), "+f"(d[51]), "+f"(d[52]), "+f"(d[53]), "+f"(d[54]), "+f"(d[55]),
      "+f"(d[56]), "+f"(d[57]), "+f"(d[58]), "+f"(d[59]), "+f"(d[60]), "+f"(d[61]), "+f"(d[62]), "+f"(d[63])
    : "r"(da), "r"(db), "r"(sc));
}

__device__ __forceinline__ void mma_ktv(float (&d)[36], uint32_t da, uint32_t db, int sc) {
  asm volatile("{\n.reg .pred p;\n.reg .b64 da, db;\nmov.b64 da, {%36, 0x40000040};\nmov.b64 db, {%37, 0x40000040};\nsetp.ne.b32 p, %38, 0;\n"
    "wgmma.mma_async.sync.aligned.m64n72k16.f32.bf16.bf16 "
    "{%0,%1,%2,%3,%4,%5,%6,%7,%8,%9,%10,%11,%12,%13,%14,%15,%16,%17,%18,%19,%20,%21,%22,%23,"
    "%24,%25,%26,%27,%28,%29,%30,%31,%32,%33,%34,%35}, "
    "da, db, p, 1, 1, 1, 1;\n}\n"
    : "+f"(d[0]), "+f"(d[1]), "+f"(d[2]), "+f"(d[3]), "+f"(d[4]), "+f"(d[5]), "+f"(d[6]), "+f"(d[7]),
      "+f"(d[8]), "+f"(d[9]), "+f"(d[10]), "+f"(d[11]), "+f"(d[12]), "+f"(d[13]), "+f"(d[14]), "+f"(d[15]),
      "+f"(d[16]), "+f"(d[17]), "+f"(d[18]), "+f"(d[19]), "+f"(d[20]), "+f"(d[21]), "+f"(d[22]), "+f"(d[23]),
      "+f"(d[24]), "+f"(d[25]), "+f"(d[26]), "+f"(d[27]), "+f"(d[28]), "+f"(d[29]), "+f"(d[30]), "+f"(d[31]),
      "+f"(d[32]), "+f"(d[33]), "+f"(d[34]), "+f"(d[35])
    : "r"(da), "r"(db), "r"(sc));
}

__device__ __forceinline__ void mma_qkvz(float (&d)[20], const uint32_t (&a)[4], uint32_t db, int sc) {
  asm volatile("{\n.reg .pred p;\n.reg .b64 db;\nmov.b64 db, {%24, 0x20};\nsetp.ne.b32 p, %25, 0;\n"
    "wgmma.mma_async.sync.aligned.m64n40k16.f32.bf16.bf16 "
    "{%0,%1,%2,%3,%4,%5,%6,%7,%8,%9,%10,%11,%12,%13,%14,%15,%16,%17,%18,%19}, "
    "{%20,%21,%22,%23}, db, p, 1, 1, 1;\n}\n"
    : "+f"(d[0]), "+f"(d[1]), "+f"(d[2]), "+f"(d[3]), "+f"(d[4]), "+f"(d[5]), "+f"(d[6]), "+f"(d[7]),
      "+f"(d[8]), "+f"(d[9]), "+f"(d[10]), "+f"(d[11]), "+f"(d[12]), "+f"(d[13]), "+f"(d[14]), "+f"(d[15]),
      "+f"(d[16]), "+f"(d[17]), "+f"(d[18]), "+f"(d[19])
    : "r"(a[0]), "r"(a[1]), "r"(a[2]), "r"(a[3]), "r"(db), "r"(sc));
}

struct Params {
  CUtensorMap x, w, xr, wo, out, gate, up, down;
};

__device__ __forceinline__ void fma8(float (&acc)[8], const uint4& w, float m) {
  acc[0] = fmaf(bf_lo(w.x), m, acc[0]); acc[1] = fmaf(bf_hi(w.x), m, acc[1]);
  acc[2] = fmaf(bf_lo(w.y), m, acc[2]); acc[3] = fmaf(bf_hi(w.y), m, acc[3]);
  acc[4] = fmaf(bf_lo(w.z), m, acc[4]); acc[5] = fmaf(bf_hi(w.z), m, acc[5]);
  acc[6] = fmaf(bf_lo(w.w), m, acc[6]); acc[7] = fmaf(bf_hi(w.w), m, acc[7]);
}
__device__ __forceinline__ float butterfly8(float (&s)[8], int lane, int o) {
#pragma unroll
  for (int k = 1; k < 8; k <<= 1) {
    const bool up = lane & (o * k);
#pragma unroll
    for (int j = 0; j < 4 / k; j++) s[j] = (up ? s[2 * j + 1] : s[2 * j]) + __shfl_xor_sync(~0u, up ? s[2 * j] : s[2 * j + 1], o * k);
  }
  return s[0];
}
constexpr int PEER = 9;
constexpr __host__ __device__ uint32_t step_list() {
  uint32_t r = 0;
  for (int j = PEER - 1; j >= 0; j--) if (j != OWN) r = r << 4 | j % 5 | (j < 5) << 3;
  return r;
}
template <bool BY_SM> struct Tile {
  int sm, tm, tn, mu;
  bool spare;
  __device__ __forceinline__ Tile() {
    if (BY_SM) asm volatile("mov.u32 %0, %%smid;" : "=r"(sm));
    else sm = blockIdx.x + (blockIdx.x >= 120) * 4;
    const int tp = sm >> 1, pr = sm & 1;
    const int v = tp < 32 ? tp : tp < 60 ? (tp * 293 - 928) >> 8 : tp * 8 - 464, g = v & 7, i = v >> 3;
    const int j = i * 11 >> 5, c = i - j * 3;
    if (MAP == 0) { tm = (v & 6) * 2 + (i & 3); tn = (v & 1) * 4 + (v >> 4 & 2) + pr; }
    if (MAP == 1) { tm = (v & 6) * 2 + (c < 2 ? j : 3); tn = (v & 1) * 4 + (c < 2 ? c : j) * 2 + pr; }
    mu = i == NOMOD ? 112 : g * 14 + (i - (i > NOMOD)) * 2 + pr;
    spare = (tp | 1) == 61;
  }
};

template <bool BY_SM> __global__ void __cluster_dims__(2, 1, 1) __launch_bounds__(NTHREADS, 1) fused_kernel(const __nv_bfloat16* __restrict__ px, Scratch* gs, const __nv_bfloat16* __restrict__ w_gate,
             const __nv_bfloat16* __restrict__ w_up, const __nv_bfloat16* __restrict__ w_r, const __nv_bfloat16* __restrict__ gate_w,
             const __grid_constant__ Params p, void* pout) {
  extern __shared__ __align__(1024) uint8_t smem[];
  const uint32_t sb = __shfl_sync(~0u, (uint32_t)__cvta_generic_to_shared(smem), 0);
  const int tid = threadIdx.x, lane = tid & 31;
  const int warp = __shfl_sync(~0u, tid >> 5, 0), wg = warp >> 2;
  const uint32_t t_start = clock32();
  const Tile<BY_SM> tile;
  const int tm = tile.tm, tn = tile.tn, mu = tile.mu, cta = tm * 8 + tn;
#define KX 0
  const int kx = KX == 1 ? (tn & 4) * 16 : KX == 2 ? (tn & 6) * 32 : KX == 3 ? (tn & 4) * 32 : KX == 4 ? (tn & 4) * 128 : KX == 5 ? (tn & 4) * 16 : 0;
  const int kx0 = KX == 5 ? 0 : KX == 6 ? (tn & 4) * 16 : kx;
  {
    const uint32_t cnt = (uint32_t)((warp & 8 ? bar_counts(16) : bar_counts(0)) >> (warp & 7) * 8);
    if (elect()) mbar_init(sb + OFF_BAR + warp * 16, cnt & 15);
    if (elect()) mbar_init(sb + OFF_BAR + warp * 16 + 8, cnt >> 4 & 15);
    if (elect()) mbar_init(sb + BAR_LAND + warp * 8, 1);
    asm volatile("fence.mbarrier_init.release.cluster;" ::: "memory");
  }
  if (warp == 0 && !tile.spare) {
#pragma unroll
    for (int s = 0; s < PRE; s++) {
      if (elect()) tma3d(sb + OFF_RING + s * STAGE_BYTES + A_BYTES, &p.w, tn * 64, s * 64 ^ kx0, 0, sb + BAR_FULL + s * 8);
      if (elect()) tma2d(sb + OFF_RING + s * STAGE_BYTES, &p.x, s * 64 ^ kx0, tm * 128, sb + BAR_FULL + s * 8);
      PROF_P(lane == 0, 64 + s);
    }
    if (elect()) {
#pragma unroll
      for (int s = 0; s < PRE; s++) { mbar_expect_tx(sb + BAR_FULL + s * 8, STAGE_BYTES); mbar_arrive(sb + BAR_FULL + s * 8); }
    }
  }
  asm volatile("" ::: "memory");
  if (warp == 5) {
#pragma unroll
    for (int i = 0; i < 4; i++) sts128(sb + OFF_ONES + i * 512 + lane * 16, 0x3F803F80u, 0x3F803F80u, 0x3F803F80u, 0x3F803F80u);
    sts32(sb + OFF_MISC + 20, 0x3FB8AA3Bu);
    fence_async_smem();
  }
  __syncthreads();
  if (tile.spare) {
    if (warp == 0) {
      const unsigned tag = (ld_relaxed(&gs->spare[tile.sm & 3]) + 1) & 0xFFF;
      const unsigned long long t0 = gtime();
      uint4 r4;
      do {
        __nanosleep(2048);
        if (gtime() - t0 > WATCHDOG_NS) __trap();
        r4 = ld_relaxed4(&gs->rslot[tile.sm & 3][lane * 4]);
      } while (!__all_sync(~0u, (((r4.x ^ tag) | (r4.y ^ tag) | (r4.z ^ tag) | (r4.w ^ tag)) & 0xFFF) == 0));
      if (tid == 0) st_relaxed(&gs->spare[tile.sm & 3], tag);
    }
    return;
  }

  if (wg == 3) {
    asm volatile("setmaxnreg.dec.sync.aligned.u32 24;");
    if (warp == 12) {
      mbar_wait(sb + BAR_W31, 0);
      mbar_wait(sb + BAR_IDX, 0);
      const uint32_t lowb = (1u << (tn & 6) * 4) - 1;
      uint32_t slabs = 0x76543210u, steps = step_list();
      const uint4* src = gs->o[tm][0];
      unsigned seen = AFLAG ? 0 : ~0u;
      if (!AFLAG) mbar_wait(sb + BAR_EMPTY + AW * 8, 1);
#pragma unroll 1
      for (int n = 8; n >= 6; n -= 2) {
#pragma unroll 1
        for (int i = 0; i < n; i++, slabs >>= 4, steps >>= 4) {
          const uint32_t s = steps & 7, full = sb + BAR_FULL + s * 8, need = 4u << (slabs & 7) * 4;
          const uint32_t land = n == 8 ? full : sb + BAR_LAND + i * 8;
          mbar_wait(full + (BAR_EMPTY - BAR_FULL), steps >> 3 & 1);
          PROF(lane == 0 && (!PROFC || n == 6), 224 + i + (n == 6) * 10);
          if (AFLAG && !__all_sync(~0u, seen & need)) {
            while (!__all_sync(~0u, (seen = ld_relaxed(gs->cnt[tm])) & need)) __nanosleep(FSL);
            if (FENCES & 1) fence_acquire();
            if (FENCES & 2) fence_async_global();
          }
          if (elect()) bulk_load(sb + OFF_RING + s * O_BYTES, src + (slabs & 7) * 1024, A_BYTES, land);
          if (elect()) mbar_expect_tx(land, A_BYTES);
          PROF(lane == 0 && (!PROFC || n == 6), 240 + i + (n == 6) * 10);
        }
        slabs = (0x76543210u & lowb) | (0x765432u & ~lowb);
        steps = 0x0CBA98u;
        src += 8 * 1024;
      }
    } else if (warp == 13) {
      uint32_t full = sb + BAR_FULL + PRE * 8, dst = sb + OFF_RING + PRE * STAGE_BYTES + A_BYTES, c0 = tn * 64, c1 = PRE * 64;
#pragma unroll 1
      for (int g = PRE; g < 32; g++) {
        if (g < 4) while ((int)(clock32() - t_start) < (g == 2 ? ST2 : ST3)) {}
        const bool reuse = (g >> 2) == 4;
        mbar_wait(full + (BAR_EMPTY - BAR_FULL), ((g >> 2) & 1) ^ 1);
        if (!reuse && elect()) tma2d(dst - A_BYTES, &p.x, c1 ^ kx, tm * 128, full);
        if (elect()) tma3d(dst, &p.w, c0, c1 ^ kx, 0, full);
        if (elect()) { mbar_expect_tx(full, reuse ? BQ_BYTES : STAGE_BYTES); mbar_arrive(full); }

        PROF_P(lane == 0, 64 + g);
        const uint32_t i = g - RT_G0;
        if (i < 4 && elect()) {
          mbar_expect_tx(sb + BAR_RT + i * 8, i ? 8192 : 8192 + 4096);
          tma2d(sb + OFF_PK + i * 8192, &p.xr, ((i + RT_ROT) & 3) * 256, cta * 16, sb + BAR_RT + i * 8);
          if (i == 0) { bulk_load(sb + OFF_KVB, w_r, 2048, sb + BAR_RT); bulk_load(sb + OFF_KVB + 2048, gate_w, 2048, sb + BAR_RT); }
        }
        const uint32_t c = g - MOD_START;
        if (c == MOD_BUFS) mbar_wait(sb + BAR_RTD, 0);
        if (c < MOD_BUFS0 && mu < MOD_CTAS && elect()) {
          PROF_P(true, 192 + c);
          const uint32_t mfull = sb + BAR_MFULL + c * 8, mdst = sb + OFF_MOD + c * 8192;
          mbar_expect_tx(mfull, c ? 8192 : 8192 + 2048);
          tma3d(mdst, &p.gate, mu * 32, c * 16, 0, mfull); tma3d(mdst + 4096, &p.up, mu * 32, c * 16, 0, mfull);
        }
        const uint32_t pc = g - PF_MOD;
        if (pc < 16 && elect()) bulk_prefetch((cta & 64 ? w_up : w_gate) + (size_t)(pc * 64 + (cta & 63)) * F_, F_ * 2);
        full += 8; dst += STAGE_BYTES; c1 += 64;
        if ((g & 3) == 3) { full -= 32; dst -= 4 * STAGE_BYTES; }
        if (g == 15) { c0 += 512; c1 = 768; }
        if (g == 19) c1 = 0;
      }
      mbar_arrive_warp(sb + BAR_W31);
      const uint32_t lowb = (1u << (tn & 6) * 4) - 1;
      uint64_t slabs = (uint64_t)((0xFEDCBA98u & lowb) | (0xFEDCBAu & ~lowb)) << 40 | (uint64_t)(8 + (tn ^ 1)) << 36 | (uint64_t)(8 + tn) << OWN * 4 |
                       (0x76543210ull & ~(~0ull << OWN * 4)) | (0x765432100ull & ~0ull << (OWN * 4 + 4));
      uint32_t ph = 1;
      c1 = 0;
#pragma unroll 1
      for (int g = 0; g < 16; g++) {
        mbar_wait(full + (BAR_EMPTY - BAR_FULL), ph);
        if (elect()) tma3d(dst, &p.wo, 0, c1, tn * 2, full);
        if (elect()) mbar_expect_tx(full, BO_BYTES);
        PROF_P(lane == 0, 96 + g);
        if (g == OWN && elect()) mbar_arrive(full);
        full += 8; dst += O_BYTES; slabs >>= 4; c1 = ((uint32_t)slabs & 15) * 64;
        if (full == sb + BAR_EMPTY) { full -= 40; dst -= 5 * O_BYTES; ph ^= 1; }
      }
    } else if (warp == 14) {
      if (mu < MOD_CTAS) {
        uint32_t full = sb + BAR_MFULL, dst = sb + OFF_MOD, ph = 0;
#pragma unroll 1
        for (int c = MOD_BUFS0; c < 24; c++) {
          mbar_wait(full + (BAR_MEMPTY - BAR_MFULL), ph);
          PROF_P(lane == 0, 192 + c);
          if (c < 16) {
            if (elect()) { tma3d(dst, &p.gate, mu * 32, c * 16, 0, full); tma3d(dst + 4096, &p.up, mu * 32, c * 16, 0, full); }
          } else if (elect()) tma3d(dst, &p.down, 0, mu * 32 + (c - 16) * 4, 0, full);
          if (elect()) mbar_expect_tx(full, 8192);
          full += 8; dst += 8192;
          if (dst == sb + OFF_PK) { full -= MOD_BUFS * 8; dst = sb + OFF_MOD; ph ^= 1; }
        }
      }
      if (elect()) {
      mbar_wait(sb + BAR_IDX, 0);
      const bool paired = PAIRED && ld_relaxed(&gs->block[cta ^ 1]) == (blockIdx.x ^ 1);
      const uint32_t pb = peer_addr(sb);
      mbar_wait(sb + BAR_EMPTY + PEER % 5 * 8, 0);
      mbar_expect_tx(sb + BAR_FULL + PEER % 5 * 8, A_BYTES);
      if (paired) mbar_arrive_peer(pb + BAR_PA);
      mbar_wait(sb + BAR_OST, 0);
      mbar_expect_tx(sb + BAR_X, 32768);
      tma2d(sb + OFF_PK, &p.x, tn * 128, tm * 128, sb + BAR_X);
      tma2d(sb + OFF_V, &p.x, tn * 128 + 64, tm * 128, sb + BAR_X);
      if (paired) {
        mbar_wait(sb + BAR_PA, 0);
        mbar_wait(sb + BAR_OWN, 0);
        bulk_push(pb + OFF_RING + PEER % 5 * O_BYTES, sb + OFF_MOD, A_BYTES, pb + BAR_FULL + PEER % 5 * 8);
        mbar_wait(sb + BAR_EMPTY + PEER % 5 * 8, 1);
        mbar_arrive_peer(pb + BAR_PA);
        mbar_wait(sb + BAR_PA, 1);
      } else {
        mbar_wait(sb + BAR_OWN, 0);
        __nanosleep(500);
        bulk_load(sb + OFF_RING + PEER % 5 * O_BYTES, gs->o[tm][8 + (tn ^ 1)], A_BYTES, sb + BAR_FULL + PEER % 5 * 8);
      }
      }
    } else if (elect()) {
#pragma unroll 1
      for (int i = 2; i < 8; i++) asm volatile("prefetch.tensormap [%0];" ::"l"(&p.x + i) : "memory");
      mbar_wait_bounded(sb + BAR_DONE, 0);
    }
  } else if (wg == 2) {
    asm volatile("setmaxnreg.dec.sync.aligned.u32 40;");
    const int mw = warp & 3;
    if (mw == 0) {
      const unsigned tag = (ld_relaxed(&gs->rslot[tn][cta]) + 1) & 0xFFF;
#pragma unroll
      for (int i = 0; i < 4; i++)
        if (lane < NCLR) ((float4*)gs)[cta * (NCLR * 4) + i * NCLR + lane] = make_float4(0.f, 0.f, 0.f, 0.f);
      if (lane == 29) gs->block[cta] = blockIdx.x;
      fence_release();
      nb_sync(NB_KEY, 160);
      const uint4 k4 = lds128(sb + OFF_MISC);
      if (lane < 8) st_relaxed(&gs->rslot[lane][cta], max(max(k4.x, k4.y), max(k4.z, k4.w)) | tag);
      if (lane < 16) st_relaxed(&gs->gslot[cta * 16 + lane], lds32(sb + OFF_G + lane * 4) | tag);
      PROF(lane == 0, 20);
      uint4 r4;
      do {
        __nanosleep(RT_SLEEP);
        r4 = ld_relaxed4(&gs->rslot[tn][lane * 4]);
      } while (!__all_sync(~0u, (((r4.x ^ tag) | (r4.y ^ tag) | (r4.z ^ tag) | (r4.w ^ tag)) & 0xFFF) == 0));
      const int c0 = 0xFFF0 - lane * 64;
      unsigned key = max(max((r4.x & 0xFFFF0000u) | (c0 + ((r4.x >> 12) & 15)), (r4.y & 0xFFFF0000u) | (c0 - 16 + ((r4.y >> 12) & 15))),
                         max((r4.z & 0xFFFF0000u) | (c0 - 32 + ((r4.z >> 12) & 15)), (r4.w & 0xFFFF0000u) | (c0 - 48 + ((r4.w >> 12) & 15))));
      key = __reduce_max_sync(~0u, key);
      if (elect()) {
        sts32(sb + OFF_MISC + 16, key);
        sts32(sb + OFF_MISC + 24, tag & 1);
        if (mu < MOD_CTAS) bulk_load(sb + OFF_XSEL, px + (size_t)(0xFFFF - (key & 0xFFFF)) * D_, 2048, sb + BAR_MFULL);
      }
      PROF(lane == 0, 21);
      do {
        r4 = ld_relaxed4(&gs->gslot[tm * 128 + lane * 4]);
      } while (!__all_sync(~0u, (((r4.x ^ tag) | (r4.y ^ tag) | (r4.z ^ tag) | (r4.w ^ tag)) & 0xFFF) == 0));
      sts128(sb + OFF_G + lane * 16, r4.x & 0xFFFF0000u, r4.y & 0xFFFF0000u, r4.z & 0xFFFF0000u, r4.w & 0xFFFF0000u);
      fence_acquire();
      __syncwarp();
      mbar_arrive_warp(sb + BAR_IDX);
    }
    PROF(tid == 256, 22);
    if (mu >= MOD_CTAS) {
      mbar_arrive_warp(sb + BAR_IDX);
      mbar_arrive_warp(sb + BAR_OA);
    } else {
      const uint32_t wp = sb + OFF_MOD + (mw >> 1) * 4096 + (mw & 1) * 512 + lane * 16;
      uint32_t mp = sb + OFF_XSEL - 128 + (mw & 1) * 64 + (lane >> 2) * 8, mc = 128;
      float acc[8] = {0.f, 0.f, 0.f, 0.f, 0.f, 0.f, 0.f, 0.f};
      uint32_t b = ~0u, ph = 0, a = sb + OFF_ONES - 3072;
      float m3 = 0.f;
      const uint32_t zero = lds32(sb + OFF_ONES) & 1;
      uint2 m = make_uint2(0, 0);
      uint4 w0 = make_uint4(0, 0, 0, 0), w1 = w0, w2 = w0, w3 = w0;
#pragma unroll 1
      for (int c = -1;; c++) {
        fma8(acc, w3, m3);
        w3 = lds128(a + 3072);
        const uint32_t rel = sb + BAR_MEMPTY + (MX > 1 ? ((0x4444210u ^ 7u << (MOD_BUFS0 - 1) * 4) >> b * 4 & 15) : b) * 8;
        if (!FIXR && c >= 0) mbar_arrive_warp(rel);
        if (c == 16) {
          const uint32_t ft = fresh_tid(), fl = ft & 31;
          sts32(sb + OFF_PART + (ft & 96) * 4 + ((ft & 3) * 8 + (fl >> 2)) * 4, __float_as_uint(butterfly8(acc, fl, 4)));
          nb_sync(NB_MODW, 128);
          const float* part = (const float*)(smem + OFF_PART) + fl;
          const float gp = bf_round(part[0] + part[32]), up = bf_round(part[64] + part[96]);
          *(__nv_bfloat16*)(smem + OFF_PART + 512 + fl * 2) = __float2bfloat16_rn(bf_round(gp * sigmoidf_(gp)) * up);
          __syncwarp();
          mp = sb + OFF_PART + 512; mc = 8;
          m = lds64(mp);
#pragma unroll
          for (int i = 0; i < 8; i++) acc[i] = 0.f;
          PROF(lane == 0 && mw == 0, 23);
        }
        if (++b == (c < MOD_BUFS0 ? MOD_BUFS0 : MOD_BUFS)) { b = 0; ph ^= 1; }
        const uint32_t ok = mbar_test(sb + BAR_MFULL + b * 8, ph);
        fma8(acc, w0, bf_lo(m.x));
        if (FIXR == 2 && c >= 0) mbar_arrive_warp(rel + ((w3.x | __float_as_uint(acc[7])) & zero));
        fma8(acc, w1, bf_hi(m.x));
        if (FIXR == 3 && c >= 0) mbar_arrive_warp(rel + ((w3.x | __float_as_uint(acc[7])) & zero));
        fma8(acc, w2, bf_lo(m.y));
        m3 = bf_hi(m.y);
        if (FIXR == 1 && c >= 0) mbar_arrive_warp(rel + (w3.x & zero));
        if (FIXR == 4 && c >= 0) mbar_arrive_warp(rel + ((w3.x | __float_as_uint(acc[7])) & zero));
        if (c == 23) break;
        if (!ok) mbar_wait(sb + BAR_MFULL + b * 8, ph);
        a = wp + b * 8192;
        mp += mc;
        m = lds64(mp);
        w0 = lds128(a); w1 = lds128(a + 1024); w2 = lds128(a + 2048);
      }
      fma8(acc, w3, m3);
      mbar_arrive_warp(sb + BAR_OA);
      float* yacc = gs->y[tn] + (fresh_tid() & 127) * 8;
      red_add4(yacc, acc[0], acc[1], acc[2], acc[3]);
      red_add4(yacc + 4, acc[4], acc[5], acc[6], acc[7]);
      PROF(lane == 0 && mw == 0, 25);
      nb_sync(NB_MODW, 128);
      if (mw == 0 && elect()) { fence_release(); red_add(gs->cnt[32], 1); }
      PROF(lane == 0 && mw == 0, 24);
    }
    const unsigned key = lds32(sb + OFF_MISC + 16);
    const int sel = 0xFFFF - (int)(key & 0xFFFF) - tm * 128;
    if (mw == 0 && sel >= 0 && sel < 128) {
      if (elect()) wait_counter(gs->cnt[32], MOD_CTAS);
      __syncwarp();
      const unsigned k16 = key >> 16;
      const float rs = bf_round(sigmoidf_(__uint_as_float(((k16 & 0x8000u) ? (k16 & 0x7FFFu) : (~k16 & 0xFFFFu)) << 16)));
      float4 v = make_float4(0.f, 0.f, 0.f, 0.f);
#pragma unroll 4
      for (int i = 0; i < 8; i++) {
        const float4 u = ld_relaxed_f4(gs->y[i] + tn * 128 + lane * 4);
        v.x += u.x; v.y += u.y; v.z += u.z; v.w += u.w;
      }
      mbar_wait(sb + BAR_X, 0);
      uint2* xp = (uint2*)(smem + OFF_PK + (lane >> 4) * 16384 + sel * 128 + ((((lane >> 1) & 7) ^ (sel & 7)) << 4) + (lane & 1) * 8);
      const uint2 xv = *xp;
      *xp = make_uint2(pack2(bf_lo(xv.x) + bf_round(bf_round(v.x) * rs), bf_hi(xv.x) + bf_round(bf_round(v.y) * rs)),
                       pack2(bf_lo(xv.y) + bf_round(bf_round(v.z) * rs), bf_hi(xv.y) + bf_round(bf_round(v.w) * rs)));
      __syncwarp();
      mbar_arrive_warp(sb + BAR_Y);
    }
  } else {
    asm volatile("setmaxnreg.inc.sync.aligned.u32 224;");
    const int w = warp & 3, wt = tid & 127;
    const int nb_self = NB_WG0 + wg;
    const uint32_t da0 = mkdesc(sb + OFF_RING, 16), db0 = mkdesc(sb + OFF_RING + A_BYTES, 8192);

    if (wg == 1) {
      float s[8] = {0.f, 0.f, 0.f, 0.f, 0.f, 0.f, 0.f, 0.f};
      const uint32_t zero = lds32(sb + OFF_ONES) & 1;
      uint32_t mask = 0xffff0000u;
#pragma unroll 1
      for (int i = 0; i < 4; i++) {
        const uint32_t u = (i + RT_ROT) & 3;
        mbar_wait(sb + BAR_RT + i * 8, 0);
        const uint4 wr = lds128(sb + OFF_KVB + u * 512 + lane * 16), gw = lds128(sb + OFF_KVB + 2048 + u * 512 + lane * 16);
        uint4 xv[4];
#pragma unroll
        for (int r = 0; r < 4; r++) xv[r] = lds128(sb + OFF_PK + i * 8192 + (w * 4 + r) * 512 + lane * 16);
        const float wf[16] = {bf_lo(wr.x), bf_hi(wr.x), bf_lo(wr.y), bf_hi(wr.y), bf_lo(wr.z), bf_hi(wr.z), bf_lo(wr.w), bf_hi(wr.w),
                              bf_lo(gw.x), bf_hi(gw.x), bf_lo(gw.y), bf_hi(gw.y), bf_lo(gw.z), bf_hi(gw.z), bf_lo(gw.w), bf_hi(gw.w)};
#pragma unroll
        for (int r = 0; r < 4; r++) {
          const uint4 xq = xv[r];
          const float xf[8] = {bf_lo(xq.x), __uint_as_float(xq.x & mask), bf_lo(xq.y), bf_hi(xq.y), bf_lo(xq.z), bf_hi(xq.z), bf_lo(xq.w), bf_hi(xq.w)};
#pragma unroll
          for (int j = 0; j < 8; j++) { s[2 * r] = fmaf(xf[j ^ 1], wf[j ^ 1], s[2 * r]); s[2 * r + 1] = fmaf(xf[j ^ 1], wf[8 + (j ^ 1)], s[2 * r + 1]); }
          mask = ((__float_as_uint(s[2 * r]) | __float_as_uint(s[2 * r + 1])) & zero) | 0xffff0000u;
        }
      }
      mbar_arrive_warp(sb + BAR_RTD);
      float v = butterfly8(s, lane, 1);
      PROF_C(wt == 0 && v != 12345.f, 19);
      v += __shfl_xor_sync(~0u, v, 8);
      v = bf_round(v + __shfl_xor_sync(~0u, v, 16));
      const unsigned rb = __float_as_uint(v) >> 16, row = w * 4 + ((lane & 7) >> 1);
      unsigned key = (lane & 1) ? 0u : ((((rb & 0x8000u) ? (~rb & 0xFFFFu) : (rb | 0x8000u)) << 16) | ((15 - row) << 12));
      key = __reduce_max_sync(~0u, key);
      if (lane == 0) sts32(sb + OFF_MISC + w * 4, key);
      if (lane < 8 && (lane & 1)) sts32(sb + OFF_G + row * 4, __float_as_uint(bf_round(sigmoidf_(v))));
      nb_arrive(NB_KEY, 160);
      nb_sync(NB_ORDER_AB, 256);
    }

    uint32_t pq[2][4][4];
    float4* const kvacc = &gs->kv[wg][tn][0][wt];
    {
      float acc[2][96];
      PROF_C(wt == 0, 1 + wg * 8);
#pragma unroll 1
      for (int g = 0; g < (SK > 1 ? 16 - SK : 16); g++) {
        const uint32_t s = g & 3;
        const uint32_t da = da0 + s * (STAGE_BYTES >> 4), db = db0 + s * (STAGE_BYTES >> 4);
        mbar_wait(sb + BAR_FULL + s * 8, (g >> 2) & 1);
        PROF_C(wt == 0, 64 + wg * 16 + g);
#pragma unroll
        for (int m = 0; m < 2; m++) {
          wg_fence();
#pragma unroll
          for (int kk = 0; kk < 4; kk++) mma_qkv(acc[m], da + (m * 512 + kk * 2), db + kk * 128, kk ? 1 : g);
          wg_commit();
          if (m == 0) {
            wg_wait<1>();
            if (g) mbar_arrive_warp(sb + BAR_EMPTY + ((g + 3) & 3) * 8);
          }
        }
      }
      auto half_step = [&](int m, int g) {
        wg_fence();
#pragma unroll
        for (int kk = 0; kk < 4; kk++)
          mma_qkv(acc[m], da0 + ((g & 3) * (STAGE_BYTES >> 4) + m * 512 + kk * 2), db0 + ((g & 3) * (STAGE_BYTES >> 4) + kk * 128), 1);
        wg_commit();
      };
#pragma unroll
      for (int g = 16 - SK; g < 16; g++) {
        mbar_wait(sb + BAR_FULL + (g & 3) * 8, 1);
        PROF_C(wt == 0, 64 + wg * 16 + g);
        half_step(0, g);
        if (g == 16 - SK) { wg_wait<1>(); mbar_arrive_warp(sb + BAR_EMPTY + ((g + 3) & 3) * 8); }
      }
      half_step(1, 16 - SK);
      half_step(1, 17 - SK);
      if (SK < 3 && wg == 0) nb_arrive(NB_ORDER_AB, 256);
      if (AREL && !wg) {
        if (SK > 1) { wg_wait<1>(); mbar_arrive_warp(sb + BAR_EMPTY + 2 * 8); }
        if (AREL == 1) { wg_wait<0>(); mbar_arrive_warp(sb + BAR_EMPTY + 3 * 8); }
      }
      mbar_wait(sb + BAR_IDX, 0);
      if (wg == 1) nb_sync(NB_STG, 256);
      wg_wait<(SK > 1 ? 2 : 1)>();
      PROF_C(wt == 0, 3 + wg * 8);

      const uint32_t st_row = (uint32_t)(w * 16 + (lane & 15)) * 128;
      uint32_t l2k[8 + PA];
#pragma unroll
      for (int u = 0; u < PA; u++) l2k[u] = 0x3FB8AA3Bu;
#pragma unroll
      for (int u = 0; u < 8; u++) {
        const int m = u >> 2, j = u & 3;
        const uint32_t a = sb + m * 8192 + st_row + ((((lane >> 4) + 2 * j) ^ (lane & 7)) << 4);
        const float* k = &acc[m][32 + 8 * j];
        const float l = __uint_as_float(l2k[u]);
        if (SK > 1 && u == M1) {
          wg_wait<1>();
          if (!AREL || wg) mbar_arrive_warp(sb + BAR_EMPTY + 2 * 8);
        }
        if (u == MM) {
          wg_wait<0>();
          if (AREL != 1 || wg) mbar_arrive_warp(sb + BAR_EMPTY + 3 * 8);
        }
        const float* v = &acc[m][64 + 8 * j];
        stsm4(a + OFF_V, pack2(v[0], v[1]), pack2(v[2], v[3]), pack2(v[4], v[5]), pack2(v[6], v[7]));
        const uint32_t r0 = phi2(k[0], k[1], l), r1 = phi2(k[2], k[3], l), r2 = phi2(k[4], k[5], l), r3 = phi2(k[6], k[7], l);
        stsm4(a + OFF_PK, r0, r1, r2, r3);
        if (u + PA < 8) l2k[u + PA] = lds32(sb + OFF_MISC + 20);
      }
      fence_async_smem();
      nb_sync(nb_self, 128);
      PROF_C(wt == 0, 8 + wg * 8);
      float c[36];
      const uint32_t dk = mkdesc(sb + OFF_PK, 16), dv = mkdesc(sb + OFF_V, OFF_ONES - OFF_V);
      wg_fence();
#pragma unroll
      for (int kk = 0; kk < 8; kk++) mma_ktv(c, dk + kk * 128, dv + (kk * 128 - (kk << 23)), kk ? 1 : 0);
      wg_commit();
      if (wg == 1) nb_arrive(NB_ORDER_BO, 256);
      auto reduce = [&](float4* dst, int gap) {
        wg_wait<0>();
        PROF_C(wt == 0, 4 + wg * 8);
        float u[18];
#pragma unroll
        for (int i = 0; i < 16; i++) u[i] = w >= 2 ? c[16 + i] : c[i];
#if NV == 6
        u[16] = c[32]; u[17] = c[34];
#pragma unroll
        for (int i = 0; i < 6; i++) {
          if (gap && i) __nanosleep(gap);
          red_add4(dst + i * 128, u[3 * i], u[3 * i + 1], u[3 * i + 2], 1.f);
        }
#else
        u[16] = __shfl_down_sync(~0u, u[15], 1);
        u[17] = lane & 2 ? c[34] : c[32];
#pragma unroll
        for (int i = 0; i < 5; i++) {
          if (gap && i) __nanosleep(gap);
          red_add4(dst + i * 128, u[3 * i], u[3 * i + 1], u[3 * i + 2], i < 3 && !(lane & 1) ? u[i == 0 ? 15 : i == 1 ? 17 : 16] : 1.f);
        }
#endif
      };
      const uint32_t zero = lds32(sb + OFF_ONES) & 1;
      float l2e = __uint_as_float(0x3FB8AA3Bu + zero);
      uint32_t dep = 0;
      float4 kv[NV];
#pragma unroll
      for (int u = 0; u < 8; u++) {
        if (u == KVE) {
          const float4* const kp = kvacc + (dep & zero);
          if (wg) {
#pragma unroll
            for (int i = 0; i < NV; i++) kv[i] = ld_relaxed_f4(kp + i * 128);
          }
          l2e = __uint_as_float(lds32(sb + OFF_MISC + 20));
        }
        if (u == PH) {
          if (PH) l2e = __uint_as_float(lds32(sb + OFF_MISC + 20 + (dep & zero)));
          if (wg) reduce(kvacc, 0);
          if (PH) l2e = __uint_as_float(lds32(sb + OFF_MISC + 20) | __float_as_uint(l2e));
          else l2e = __uint_as_float(lds32(sb + OFF_MISC + 20));
        }
#pragma unroll
        for (int i = 0; i < 4; i++) dep |= pq[u >> 2][u & 3][i] = phi2(acc[u >> 2][8 * (u & 3) + 2 * i], acc[u >> 2][8 * (u & 3) + 2 * i + 1], l2e);
      }
      float4* const kvp = kvacc + (dep & zero);
      if (!wg) reduce(kvp, RED_SLEEP);
      PROF_C(wt == 0 && kvp == kvacc, 34 + wg * 2);
      for (int tries = wg ? 0 : 9;; tries++) {
        if (tries > RETRY)
          while (ld_relaxed((const unsigned*)&(kvp - lane)[NV * 128 - 128 + 31].w) != 0x41800000u) __nanosleep(wg ? KV_SLEEP : KV_SLEEP_A);
        if (KVE == 8 || tries) {
#pragma unroll
          for (int i = 0; i < NV; i++) kv[i] = ld_relaxed_f4(kvp + i * 128);
        }
        const uint32_t kb = sb + OFF_KVB + (w >> 1) * 2560 + (w & 1) * 256;
        const uint32_t ka = kb + (lane >> 4) * 512 + (lane & 15) * 16;
        stsm4(ka, pack2(kv[0].x, kv[0].y), pack2(kv[0].z, kv[1].x), pack2(kv[1].y, kv[1].z), pack2(kv[2].x, kv[2].y));
#if NV == 6
        stsm4(ka + 1024, pack2(kv[2].z, kv[3].x), pack2(kv[3].y, kv[3].z), pack2(kv[4].x, kv[4].y), pack2(kv[4].z, kv[NV - 1].x));
        sts32(kb + 2048 + lane * 4, pack2(kv[NV - 1].y, kv[NV - 1].y));
        sts32(kb + 2048 + 128 + lane * 4, pack2(kv[NV - 1].z, kv[NV - 1].z));
        const bool ok = kv[0].w + kv[1].w + kv[2].w + kv[3].w + kv[4].w + kv[NV - 1].w == 96.f;
#else
        const uint32_t zz = pack2(kv[1].w, kv[1].w);
        if (!(lane & 1)) sts128(kb + 2048 + (lane & 2) * 64 + (lane >> 2) * 16, zz, zz, zz, zz);
        const float u15 = __shfl_up_sync(~0u, kv[2].w, 1);
        stsm4(ka + 1024, pack2(kv[2].z, kv[3].x), pack2(kv[3].y, kv[3].z), pack2(kv[4].x, kv[4].y), pack2(kv[4].z, lane & 1 ? u15 : kv[0].w));
        const bool ok = !(lane & 1) || kv[0].w + kv[1].w + kv[2].w + kv[3].w + kv[4].w == 80.f;
#endif
        if (__all_sync(~0u, ok)) { PROF_V(wg && lane == 0, 40 + w, tries * 100 + 2); break; }
      }
    }
    {
      PROF_C(wt == 0, 5 + wg * 8);
      fence_async_smem();
      nb_sync(nb_self, 128);
      float o[2][2][20];
      const uint32_t dz = mkdesc(sb + OFF_KVB, 128);
      wg_fence();
#pragma unroll
      for (int m = 0; m < 2; m++) {
#pragma unroll
        for (int h = 0; h < 2; h++)
#pragma unroll
          for (int kk = 0; kk < 2; kk++) mma_qkvz(o[m][h], pq[m][2 * h + kk], dz + (h * 160 + kk * 16), kk);
        wg_commit();
      }
      const uint32_t tmask = (lane & 3) == (lane >> 3), tbit = lds32(sb + OFF_MISC + 24) & tmask;
      float gr[2][2], sc[4];
#pragma unroll
      for (int i = 0; i < 4; i++) gr[i >> 1][i & 1] = __uint_as_float(lds32(sb + OFF_G + ((i >> 1) * 64 + (i & 1) * 8 + w * 16 + (lane >> 2)) * 4));
      if (wg == 1) {
        mbar_arrive_warp(sb + BAR_OST);
        mbar_wait(sb + BAR_OA, 0);
      }
      const uint32_t os = sb + (wg ? OFF_MOD : OFF_PK) + w * 2048;
      uint8_t* const og = (uint8_t*)gs->o[tm][wg * 8 + tn] + w * 2048;
#pragma unroll
      for (int m = 0; m < 2; m++) {
        if (m == 0) wg_wait<1>();
        if (m == 0) PROF_C(wt == 0, 6 + wg * 8);
#pragma unroll
        for (int h = 0; h < 2; h++) {
          const float* oo = o[m][h];
          uint32_t pin = 0;
          if (!m && h) {
            wg_wait<0>();
#pragma unroll
            for (int i = 0; i < 4; i++) pin |= __float_as_uint(sc[i] = gr[1][i & 1] * rcp(o[1][i >> 1][16 + (i & 1) * 2] + 1e-6f));
            pin &= __float_as_uint(gr[0][0]) & 16;
          }
          const float s0 = m ? sc[2 * h] : gr[m][0] * rcp(oo[16] + 1e-6f), s1 = m ? sc[2 * h + 1] : gr[m][1] * rcp(oo[18] + 1e-6f);
#pragma unroll
          for (int j = 0; j < 2; j++)
            stsm4(os + m * 8192 + (lane & 15) * 128 + ((((lane >> 4) + 4 * h + 2 * j) ^ (lane & 7)) << 4) + (j ? pin : 0),
                  (pack2(oo[8 * j] * s0, oo[8 * j + 1] * s0) & ~tmask) | tbit, (pack2(oo[8 * j + 2] * s1, oo[8 * j + 3] * s1) & ~tmask) | tbit,
                  pack2(oo[8 * j + 4] * s0, oo[8 * j + 5] * s0), pack2(oo[8 * j + 6] * s1, oo[8 * j + 7] * s1));
        }
        fence_async_smem();
        __syncwarp();
        if (elect()) bulk_store(og + m * 8192, os + m * 8192, 2048);
      }
      if (elect()) {
        bulk_commit();
        if (wg) mbar_arrive(sb + BAR_OWN);
        PROF(wt == 0, 7 + wg * 8);
        if (AFLAG && !wg) red_add(gs->cnt[tm], 1u << tn * 4);
        asm volatile("cp.async.bulk.wait_group.read 0;" ::: "memory");
        PROF(wt == 0, 17 + wg);
        PROF(wt == 96, 38 + wg);
      }
    }

    __syncwarp();
    const uint32_t par = lds32(sb + OFF_MISC + 24), cw = lane * 32 + (lane & 4) * 4 + (lane >> 3) * 4;
    auto check_tile = [&](int g, uint32_t s) {
      const uint32_t a = sb + OFF_RING + s * O_BYTES + w * 2048, fix = sb + BAR_FIX + warp * 8;
      for (;;) {
        const uint32_t u0 = lds32(a + cw), u1 = lds32(a + cw + 1024), u2 = lds32(a + cw + 8192), u3 = lds32(a + cw + 9216);
        if (__all_sync(~0u, !(mism(mism(u0, u1, par), mism(u2, u3, par), 0) & 1))) break;
        PROF_V(lane == 0, 44 + g, 102);
        const int slab = g < OWN ? g : g < PEER ? g - 1 : g == PEER ? 8 + (tn ^ 1) : g - 10 < (tn & 6) ? g - 2 : g;
        const uint4* src = gs->o[tm][slab] + w * 128;
        const uint32_t ph = !mbar_test(fix, 1);
        fence_async_smem();
        __syncwarp();
        if (elect()) { mbar_expect_tx(fix, 4096); bulk_load(a, src, 2048, fix); bulk_load(a + 8192, src + 512, 2048, fix); }
        mbar_wait(fix, ph);
      }
    };
    if (wg == 1) {
#pragma unroll 1
      for (int g = 10; g < 16; g++) {
        const uint32_t s = g == 15 ? 0 : g - 10;
        mbar_wait(sb + BAR_LAND + (g - 10) * 8, 0);
        PROF_C(wt == 0, 214 + g);
        check_tile(g, s);
        if (w) nb_arrive(NB_CHK + (g & 1), 128);
        else { nb_sync(NB_CHK + (g & 1), 128); mbar_arrive_warp(sb + BAR_FULL + s * 8); }
        if (g & 1) nb_sync(nb_self, 128);
      }
    } else {
      nb_arrive(NB_STG, 256);
      float acc[2][64];
      mbar_wait(sb + BAR_W31, 0);
#pragma unroll 1
      for (int g = 0; g < PC; g++) { mbar_wait(sb + BAR_EMPTY + g * 8, 1); mbar_wait(sb + BAR_FULL + g * 8, 0); check_tile(g, g); }
      nb_sync(NB_ORDER_BO, 256);
      PROF_C(wt == 0, 26);
      uint32_t xr[2][8][4], q[2][2];
      const uint32_t ta = sb + OFF_PK + (uint32_t)(w * 16 + (lane & 15)) * 128;
#pragma unroll 1
      for (int g = 0; g < 13 - TL; g++) {
        const uint32_t r = g * 52 >> 8, s = g - r * 5;
        const uint32_t da = da0 + (g == OWN ? 5 : s) * (O_BYTES >> 4), db = db0 + s * (O_BYTES >> 4);
        if (g == OWN) {
          wg_wait<0>();
          mbar_arrive_warp(sb + BAR_EMPTY + (OWN + 4) % 5 * 8);
          mbar_wait(sb + BAR_OWN, 0);
        }
        mbar_wait(sb + BAR_FULL + s * 8, r & 1);
        if (g != OWN && g >= PC) check_tile(g, s);
        PROF_C(wt == 0, 96 + g);
        wg_fence();
#pragma unroll
        for (int kk = 0; kk < 4; kk++)
#pragma unroll
          for (int m = 0; m < 2; m++) mma_out(acc[m], da + (m * 512 + kk * 2), db + kk * 128, kk ? 1 : g);
        wg_commit();
        wg_wait<1>();
        if (~(1 | 1 << OWN) >> g & 1) mbar_arrive_warp(sb + BAR_EMPTY + (s ? s - 1 : 4) * 8);
      }
      mbar_wait(sb + BAR_X, 0);
      if (((0xFFFF - (lds32(sb + OFF_MISC + 16) & 0xFFFF)) >> 7) == tm) mbar_wait(sb + BAR_Y, 0);
#pragma unroll
      for (int u = 0; u < 4; u++) {
        const int m = u >> 1, g = 13 - TL + u;
        const float g1 = 1.f - __uint_as_float(lds32(sb + OFF_G + (m * 64 + w * 16 + (u & 1) * 8 + (lane >> 2)) * 4));
        q[m][u & 1] = pack2(g1, g1);
#pragma unroll
        for (int j = 0; j < 4; j++) ldsm4(ta + (u & 1) * 16384 + m * 8192 + ((((lane >> 4) + 2 * j) ^ (lane & 7)) << 4), xr[m][(u & 1) * 4 + j]);
        if (u == 3) break;
        mbar_wait(sb + BAR_FULL + g % 5 * 8, g / 5 & 1);
        PROF_C(wt == 0, 96 + g);
        wg_fence();
#pragma unroll
        for (int kk = 0; kk < 4; kk++)
#pragma unroll
          for (int mm = 0; mm < 2; mm++)
            mma_out(acc[mm], da0 + (g % 5 * (O_BYTES >> 4) + mm * 512 + kk * 2), db0 + (g % 5 * (O_BYTES >> 4) + kk * 128), 1);
        wg_commit();
        wg_wait<1>();
        if (g <= 11) mbar_arrive_warp(sb + BAR_EMPTY + (g + 4) % 5 * 8);
      }
      auto half_step = [&](int m, int g) {
        if (m == 0) { mbar_wait(sb + BAR_FULL + g % 5 * 8, g / 5 & 1); PROF_C(wt == 0, 96 + g); wg_fence(); }
#pragma unroll
        for (int kk = 0; kk < 4; kk++)
          mma_out(acc[m], da0 + (g % 5 * (O_BYTES >> 4) + m * 512 + kk * 2), db0 + (g % 5 * (O_BYTES >> 4) + kk * 128), 1);
      };
      auto stage = [&](int m, int j0, int j1) {
#pragma unroll
        for (int j = j0; j < j1; j++) {
          const float* v = &acc[m][8 * j];
          stsm4(ta + (j >> 2) * 16384 + m * 8192 + ((((lane >> 4) + 2 * (j & 3)) ^ (lane & 7)) << 4),
                fma_bf2(xr[m][j][0], q[m][0], pack2(v[0], v[1])), fma_bf2(xr[m][j][1], q[m][1], pack2(v[2], v[3])),
                fma_bf2(xr[m][j][2], q[m][0], pack2(v[4], v[5])), fma_bf2(xr[m][j][3], q[m][1], pack2(v[6], v[7])));
        }
      };
      auto leave_tma = [&](int m, int h) {
        fence_async_smem();
        __syncwarp();
        if (elect()) tma2d_store(&p.out, sb + OFF_PK + h * 16384 + m * 8192 + w * 2048, tn * 128 + h * 64, tm * 128 + m * 64 + w * 16);
      };
      auto fetch = [&](int m, int h, uint4 (&v)[4]) {
        __syncwarp();
        const uint32_t r = lane >> 3;
#pragma unroll
        for (int i = 0; i < 4; i++) v[i] = lds128(sb + OFF_PK + h * 16384 + m * 8192 + w * 2048 + (r + 4 * i) * 128 + (((lane ^ (r + 4 * i)) & 7) << 4));
      };
      auto leave = [&](int m, int h, const uint4 (&v)[4]) {
        char* const dst = (char*)pout + (size_t)(tm * 128 + m * 64 + w * 16 + (lane >> 3)) * (D_ * 2) + tn * 256 + h * 128 + (lane & 7) * 16;
#pragma unroll
        for (int i = 0; i < 4; i++) asm volatile("st.global" STQ ".v4.u32 [%0], {%1, %2, %3, %4};" ::"l"(dst + i * 4 * D_ * 2), "r"(v[i].x), "r"(v[i].y), "r"(v[i].z), "r"(v[i].w) : "memory");
      };
#pragma unroll
      for (int g = 16 - TL; g < 16; g++) half_step(0, g);
      wg_commit();
#pragma unroll
      for (int g = 16 - TL; g < 16 - TL + TQ; g++) half_step(1, g);
      wg_commit();
      mbar_arrive_warp(sb + BAR_DONE);
      wg_wait<1>();
      PROF(wt == 0, 35);
      stage(0, 0, 4);
      leave_tma(0, 0);
      if (TQ < TL) {
        wg_fence();
#pragma unroll
        for (int g = 16 - TL + TQ; g < 16; g++) half_step(1, g);
        wg_commit();
      }
      stage(0, 4, 8);
      leave_tma(0, 1);
      if (elect()) bulk_commit();
      PROF(wt == 0, 33);
      wg_wait<0>();
      PROF(wt == 0, 31);
      uint4 v0[4], v1[4];
      stage(1, 0, 4);
      if (ILV == 0) { fetch(1, 0, v0); leave(1, 0, v0); stage(1, 4, 8); fetch(1, 1, v1); leave(1, 1, v1); }
      if (ILV == 1) { fetch(1, 0, v0); stage(1, 4, 8); leave(1, 0, v0); fetch(1, 1, v1); leave(1, 1, v1); }
      if (ILV == 2) { fetch(1, 0, v0); stage(1, 4, 6); leave(1, 0, v0); stage(1, 6, 8); fetch(1, 1, v1); leave(1, 1, v1); }
      if (ILV == 3) { stage(1, 4, 8); fetch(1, 0, v0); fetch(1, 1, v1); leave(1, 0, v0); leave(1, 1, v1); }
      if (elect()) asm volatile("cp.async.bulk.wait_group.read 0;" ::: "memory");
      PROF(wt == 0, 32);
    }
  }
}

typedef CUresult (*EncodeFn)(CUtensorMap*, CUtensorMapDataType, cuuint32_t, void*, const cuuint64_t*, const cuuint64_t*, const cuuint32_t*,
                             const cuuint32_t*, CUtensorMapInterleave, CUtensorMapSwizzle, CUtensorMapL2promotion, CUtensorMapFloatOOBfill);

void encode(EncodeFn fn, CUtensorMap* m, const void* ptr, int rank, const cuuint64_t* dims, const cuuint64_t* strides, const cuuint32_t* box,
            CUtensorMapSwizzle sw, CUtensorMapDataType dt = CU_TENSOR_MAP_DATA_TYPE_BFLOAT16, CUtensorMapL2promotion pr = CU_TENSOR_MAP_L2_PROMOTION_L2_128B) {
  const cuuint32_t es[3] = {1, 1, 1};
  fn(m, dt, rank, const_cast<void*>(ptr), dims, strides, box, es, CU_TENSOR_MAP_INTERLEAVE_NONE, sw,
     pr, CU_TENSOR_MAP_FLOAT_OOB_FILL_NONE);
}

}

extern "C" void kernel_launch(void* const* d_in, const int* in_sizes, int n_in, void* d_out, int out_size) {
  (void)in_sizes; (void)n_in; (void)out_size;
  EncodeFn fn = nullptr;
  cudaDriverEntryPointQueryResult qr;
  cudaGetDriverEntryPoint("cuTensorMapEncodeTiled", (void**)&fn, cudaEnableDefault, &qr);

  Params p;
  {
    const cuuint64_t dims[2] = {D_, S_}, str[1] = {D_ * 2};
    const cuuint32_t box[2] = {64, 128}, box_st[2] = {64, 16}, box_r[2] = {256, 16};
    encode(fn, &p.xr, d_in[0], 2, dims, str, box_r, CU_TENSOR_MAP_SWIZZLE_NONE);
#define XPROMO CU_TENSOR_MAP_L2_PROMOTION_L2_128B
    encode(fn, &p.x, d_in[0], 2, dims, str, box, CU_TENSOR_MAP_SWIZZLE_128B, CU_TENSOR_MAP_DATA_TYPE_BFLOAT16, XPROMO);
    encode(fn, &p.out, d_out, 2, dims, str, box_st, CU_TENSOR_MAP_SWIZZLE_128B);
  }
  {
    const cuuint64_t dims[3] = {D_, D_, 3}, str[2] = {3 * D_ * 2, D_ * 2};
    const cuuint32_t box[3] = {64, 64, 3};
    encode(fn, &p.w, d_in[1], 3, dims, str, box, CU_TENSOR_MAP_SWIZZLE_128B);
  }
  {
    const cuuint64_t dims[3] = {64, D_, D_ / 64}, str[2] = {D_ * 2, 128};
    const cuuint32_t box[3] = {64, 64, 2};
    encode(fn, &p.wo, d_in[2], 3, dims, str, box, CU_TENSOR_MAP_SWIZZLE_128B);
  }
  {
    const cuuint64_t dims[3] = {F_, D_ / 4, 4}, str[2] = {F_ * 8, F_ * 2};
    const cuuint32_t box[3] = {32, 16, 4};
    encode(fn, &p.gate, d_in[5], 3, dims, str, box, CU_TENSOR_MAP_SWIZZLE_NONE);
    encode(fn, &p.up, d_in[6], 3, dims, str, box, CU_TENSOR_MAP_SWIZZLE_NONE);
  }
  {
    const cuuint64_t dims[3] = {D_ / 4, F_, 2}, str[2] = {D_ * 2, D_};
    const cuuint32_t box[3] = {256, 4, 2};
    encode(fn, &p.down, d_in[7], 3, dims, str, box, CU_TENSOR_MAP_SWIZZLE_NONE, CU_TENSOR_MAP_DATA_TYPE_UINT32);
  }
  void* gs = nullptr;
  cudaGetSymbolAddress(&gs, g_scratch);
  typedef const __nv_bfloat16* bp;
  int dev = 0, sms = 0;
  cudaGetDevice(&dev);
  cudaDeviceGetAttribute(&sms, cudaDevAttrMultiProcessorCount, dev);
  const bool by_sm = BYSM && sms == NGRID;
  const auto kernel = by_sm ? fused_kernel<true> : fused_kernel<false>;
  cudaFuncSetAttribute(kernel, cudaFuncAttributeMaxDynamicSharedMemorySize, SMEM_BYTES);
  kernel<<<by_sm ? NGRID : NCTA, NTHREADS, SMEM_BYTES, cudaStreamPerThread>>>((bp)d_in[0], (Scratch*)gs, (bp)d_in[5], (bp)d_in[6], (bp)d_in[4], (bp)d_in[8], p, d_out);
}
```

```cpp
#include <cuda_runtime.h>
#include <cuda.h>
#include <cuda_bf16.h>
#include <stdint.h>
#include <stddef.h>

namespace {

constexpr int S_ = 2048, D_ = 1024, F_ = 3584;
constexpr int NCTA = 128, NGRID = 132, NTHREADS = 512;
constexpr int MOD_CTAS = F_ / 32;

#define PC 2
#define PRE 2
#define ST1 700
#define RT_G0 2
#define RT_ROT 2
#define RT_SLEEP 500
#define PF_MOD 6
#define MOD_START 9
#define MM 4
#define PA 4
#define RED_SLEEP 32
#define RETRY 1
#define KV_SLEEP_A 128
#define KV_SLEEP 50
#define OWN 5
#define TL 3
#define NOMOD 5
#define FSL 128
#define M1 1
#define PAIRED 1
#define BYSM 1

constexpr uint32_t A_BYTES = 16384, BQ_BYTES = 24576, BO_BYTES = 16384, STAGE_BYTES = A_BYTES + BQ_BYTES, O_BYTES = A_BYTES + BO_BYTES;
constexpr int MOD_BUFS = 3, MOD_BUFS0 = MOD_BUFS + 1;
static_assert(MOD_START + MOD_BUFS0 <= 16, "first FFN round is requested during wave A");
constexpr uint32_t OFF_RING = 0;
constexpr uint32_t OFF_MOD = 4 * STAGE_BYTES;
constexpr uint32_t OFF_PK = OFF_MOD + MOD_BUFS * 8192;
constexpr uint32_t OFF_V = OFF_PK + 16384;
constexpr uint32_t OFF_ONES = OFF_V + 16384;
constexpr uint32_t OFF_KVB = OFF_ONES + 2048;
constexpr uint32_t OFF_XSEL = OFF_KVB + 5120;
constexpr uint32_t OFF_G = OFF_XSEL + 2048;
constexpr uint32_t OFF_PART = OFF_G + 512;
constexpr uint32_t OFF_MISC = OFF_PART + 576;
constexpr uint32_t OFF_BAR = OFF_MISC + 32;
constexpr uint32_t BAR_FULL = OFF_BAR, BAR_EMPTY = OFF_BAR + 40, BAR_RTD = OFF_BAR + 80, BAR_Y = OFF_BAR + 88, BAR_DONE = OFF_BAR + 96,
                   BAR_X = OFF_BAR + 104, BAR_OA = OFF_BAR + 112, BAR_OWN = OFF_BAR + 120, BAR_OST = OFF_BAR + 128, BAR_PA = OFF_BAR + 136,
                   BAR_W31 = OFF_BAR + 144, BAR_MFULL = OFF_BAR + 152, BAR_MEMPTY = BAR_MFULL + MOD_BUFS0 * 8,
                   BAR_IDX = BAR_MEMPTY + MOD_BUFS * 8;
constexpr uint32_t SMEM_BYTES = OFF_BAR + 384;
static_assert(SMEM_BYTES <= 232448, "smem");

constexpr uint32_t BAR_LAND = OFF_BAR + 256, BAR_FIX = BAR_LAND + 64;
constexpr uint32_t BAR_RT = BAR_FIX;
static_assert(TL == 3 && PRE == 2 && BAR_IDX - OFF_BAR < 256, "warp w initialises barriers 2w and 2w + 1");
constexpr __host__ __device__ uint64_t bar_counts(int first) {
  uint64_t r = 0;
  for (uint32_t i = 0; i < 16; i++) {
    const uint32_t b = OFF_BAR + (first + i) * 8;
    const uint64_t c = b < BAR_EMPTY ? 2 : b == BAR_IDX ? 5 : b == BAR_Y || b == BAR_X || (b >= BAR_PA && b < BAR_MEMPTY) ? 1 : 4;
    r |= c << i * 4;
  }
  return r;
}

constexpr int NB_WG0 = 1, NB_ORDER_AB = 3, NB_ORDER_BO = 4, NB_STG = 5, NB_MODW = 6, NB_KEY = 7, NB_CHK = 8;

constexpr int NV = 5, NCLR = NV * 4 + 5;
struct Scratch {
  float4 kv[2][8][NV][128];
  float y[8][D_];
  unsigned cnt[64][32];
  unsigned gslot[S_];
  unsigned rslot[8][NCTA];
  unsigned spare[128];
  unsigned block[NCTA];
  uint4 o[16][16][1024];
};
static_assert(offsetof(Scratch, gslot) == NCTA * NCLR * 64, "clear size");
__device__ __align__(1024) Scratch g_scratch;

#define PROF(cond, i) do {} while (0)
#define PROF_C(cond, i) do {} while (0)
#define PROF_P(cond, i) do {} while (0)
#define PROF_V(cond, i, v) do {} while (0)

__device__ __forceinline__ void mbar_init(uint32_t bar, int cnt) { asm volatile("mbarrier.init.shared::cta.b64 [%0], %1;" ::"r"(bar), "r"(cnt)); }
__device__ __forceinline__ void mbar_expect_tx(uint32_t bar, uint32_t bytes) { asm volatile("mbarrier.arrive.expect_tx.shared::cta.b64 _, [%0], %1;" ::"r"(bar), "r"(bytes) : "memory"); }
__device__ __forceinline__ void mbar_arrive(uint32_t bar) { asm volatile("mbarrier.arrive.shared::cta.b64 _, [%0];" ::"r"(bar) : "memory"); }
__device__ __forceinline__ uint32_t peer_addr(uint32_t a) {
  uint32_t r;
  asm volatile("{\n.reg .u32 c;\nmov.u32 c, %%cluster_ctarank;\nxor.b32 c, c, 1;\nmapa.shared::cluster.u32 %0, %1, c;\n}" : "=r"(r) : "r"(a));
  return r;
}
__device__ __forceinline__ void mbar_arrive_peer(uint32_t bar) { asm volatile("mbarrier.arrive.shared::cluster.b64 _, [%0];" ::"r"(bar) : "memory"); }
__device__ __forceinline__ uint32_t mism(uint32_t a, uint32_t b, uint32_t p) {
  uint32_t r; asm("lop3.b32 %0, %1, %2, %3, 0x7E;" : "=r"(r) : "r"(a), "r"(b), "r"(p)); return r;
}
__device__ __forceinline__ bool elect() {
  uint32_t r;
  asm volatile("{\n.reg .pred p;\nelect.sync _|p, 0xffffffff;\nselp.u32 %0, 1, 0, p;\n}" : "=r"(r));
  return r;
}
__device__ __forceinline__ uint32_t fresh_tid() { uint32_t r; asm volatile("mov.u32 %0, %%tid.x;" : "=r"(r)); return r; }
__device__ __forceinline__ void mbar_arrive_warp(uint32_t bar) {
  asm volatile("{\n.reg .pred p;\nelect.sync _|p, 0xffffffff;\n@p mbarrier.arrive.shared::cta.b64 _, [%0];\n}" ::"r"(bar) : "memory");
}
__device__ __forceinline__ void mbar_wait(uint32_t bar, uint32_t parity) {
  asm volatile("{\n.reg .pred p;\nWAIT_L:\nmbarrier.try_wait.parity.shared::cta.b64 p, [%0], %1;\n@p bra DONE_L;\nbra WAIT_L;\nDONE_L:\n}"
               ::"r"(bar), "r"(parity) : "memory");
}
__device__ __forceinline__ uint32_t mbar_test(uint32_t bar, uint32_t parity) {
  uint32_t ok;
  asm volatile("{\n.reg .pred p;\nmbarrier.test_wait.parity.shared::cta.b64 p, [%1], %2;\nselp.u32 %0, 1, 0, p;\n}" : "=r"(ok) : "r"(bar), "r"(parity) : "memory");
  return ok;
}
constexpr unsigned long long WATCHDOG_NS = 2000000000ull;
__device__ __forceinline__ unsigned long long gtime() { unsigned long long t; asm volatile("mov.u64 %0, %%globaltimer;" : "=l"(t)); return t; }
__device__ __forceinline__ uint32_t clock32() { uint32_t t; asm volatile("mov.u32 %0, %%clock;" : "=r"(t)); return t; }
__device__ __forceinline__ void mbar_wait_bounded(uint32_t bar, uint32_t parity) {
  unsigned long long t0 = 0;
  for (;;) {
    uint32_t ok;
    asm volatile("{\n.reg .pred p;\nmbarrier.try_wait.parity.shared::cta.b64 p, [%1], %2;\nselp.u32 %0, 1, 0, p;\n}" : "=r"(ok) : "r"(bar), "r"(parity) : "memory");
    if (ok) break;
    const unsigned long long t1 = gtime();
    if (t0 == 0) t0 = t1;
    if (t1 - t0 > WATCHDOG_NS) __trap();
  }
}
__device__ __forceinline__ void tma2d(uint32_t dst, const CUtensorMap* m, int c0, int c1, uint32_t bar) {
  asm volatile("cp.async.bulk.tensor.2d.shared::cluster.global.mbarrier::complete_tx::bytes [%0], [%1, {%3, %4}], [%2];"
               ::"r"(dst), "l"(m), "r"(bar), "r"(c0), "r"(c1) : "memory");
}
__device__ __forceinline__ void tma3d(uint32_t dst, const CUtensorMap* m, int c0, int c1, int c2, uint32_t bar) {
  asm volatile("cp.async.bulk.tensor.3d.shared::cluster.global.mbarrier::complete_tx::bytes [%0], [%1, {%3, %4, %5}], [%2];"
               ::"r"(dst), "l"(m), "r"(bar), "r"(c0), "r"(c1), "r"(c2) : "memory");
}
__device__ __forceinline__ void bulk_load(uint32_t dst, const void* src, uint32_t bytes, uint32_t bar) {
  asm volatile("cp.async.bulk.shared::cluster.global.mbarrier::complete_tx::bytes [%0], [%1], %2, [%3];" ::"r"(dst), "l"(src), "r"(bytes), "r"(bar) : "memory");
}
__device__ __forceinline__ void bulk_store(void* dst, uint32_t src, uint32_t bytes) {
  asm volatile("cp.async.bulk.global.shared::cta.bulk_group [%0], [%1], %2;" ::"l"(dst), "r"(src), "r"(bytes) : "memory");
}
__device__ __forceinline__ void bulk_push(uint32_t dst, uint32_t src, uint32_t bytes, uint32_t bar) {
  asm volatile("cp.async.bulk.shared::cluster.shared::cta.mbarrier::complete_tx::bytes [%0], [%1], %2, [%3];" ::"r"(dst), "r"(src), "r"(bytes), "r"(bar) : "memory");
}
__device__ __forceinline__ void bulk_commit() { asm volatile("cp.async.bulk.commit_group;" ::: "memory"); }
__device__ __forceinline__ void bulk_prefetch(const void* p, uint32_t bytes) {
  asm volatile("cp.async.bulk.prefetch.L2.global [%0], %1;" ::"l"(p), "r"(bytes) : "memory");
}
__device__ __forceinline__ void tma2d_store(const CUtensorMap* m, uint32_t src, int c0, int c1) {
  asm volatile("cp.async.bulk.tensor.2d.global.shared::cta.bulk_group [%0, {%2, %3}], [%1];" ::"l"(m), "r"(src), "r"(c0), "r"(c1) : "memory");
}
__device__ __forceinline__ void wg_fence() { asm volatile("wgmma.fence.sync.aligned;" ::: "memory"); }
__device__ __forceinline__ void wg_commit() { asm volatile("wgmma.commit_group.sync.aligned;" ::: "memory"); }
template <int N> __device__ __forceinline__ void wg_wait() { asm volatile("wgmma.wait_group.sync.aligned %0;" ::"n"(N) : "memory"); }
__device__ __forceinline__ void fence_async_smem() { asm volatile("fence.proxy.async.shared::cta;" ::: "memory"); }
__device__ __forceinline__ void fence_release() { asm volatile("fence.release.gpu;" ::: "memory"); }
__device__ __forceinline__ void fence_acquire() { asm volatile("fence.acquire.gpu;" ::: "memory"); }
__device__ __forceinline__ void nb_sync(int id, int n) { asm volatile("bar.sync %0, %1;" ::"r"(id), "r"(n) : "memory"); }
__device__ __forceinline__ void nb_arrive(int id, int n) { asm volatile("bar.arrive %0, %1;" ::"r"(id), "r"(n) : "memory"); }
__device__ __forceinline__ void stsm4(uint32_t addr, uint32_t r0, uint32_t r1, uint32_t r2, uint32_t r3) {
  asm volatile("stmatrix.sync.aligned.m8n8.x4.shared.b16 [%0], {%1, %2, %3, %4};" ::"r"(addr), "r"(r0), "r"(r1), "r"(r2), "r"(r3) : "memory");
}
__device__ __forceinline__ void sts128(uint32_t addr, uint32_t a, uint32_t b, uint32_t c, uint32_t d) {
  asm volatile("st.shared.v4.b32 [%0], {%1, %2, %3, %4};" ::"r"(addr), "r"(a), "r"(b), "r"(c), "r"(d) : "memory");
}
__device__ __forceinline__ uint32_t pack2(float lo, float hi) {
  uint32_t r; asm("cvt.rn.bf16x2.f32 %0, %1, %2;" : "=r"(r) : "f"(hi), "f"(lo)); return r;
}
__device__ __forceinline__ float bf_lo(uint32_t v) { return __uint_as_float(v << 16); }
__device__ __forceinline__ float bf_hi(uint32_t v) { return __uint_as_float(v & 0xffff0000u); }
__device__ __forceinline__ float bf_round(float v) { return __bfloat162float(__float2bfloat16_rn(v)); }
__device__ __forceinline__ void ldsm4(uint32_t addr, uint32_t (&r)[4]) {
  asm volatile("ldmatrix.sync.aligned.m8n8.x4.shared.b16 {%0, %1, %2, %3}, [%4];" : "=r"(r[0]), "=r"(r[1]), "=r"(r[2]), "=r"(r[3]) : "r"(addr) : "memory");
}
__device__ __forceinline__ uint4 lds128(uint32_t addr) {
  uint4 v; asm volatile("ld.volatile.shared.v4.u32 {%0, %1, %2, %3}, [%4];" : "=r"(v.x), "=r"(v.y), "=r"(v.z), "=r"(v.w) : "r"(addr) : "memory"); return v;
}
__device__ __forceinline__ uint2 lds64(uint32_t addr) { uint2 v; asm volatile("ld.volatile.shared.v2.u32 {%0, %1}, [%2];" : "=r"(v.x), "=r"(v.y) : "r"(addr) : "memory"); return v; }
__device__ __forceinline__ uint32_t lds32(uint32_t addr) { uint32_t v; asm volatile("ld.volatile.shared.u32 %0, [%1];" : "=r"(v) : "r"(addr) : "memory"); return v; }
__device__ __forceinline__ void sts32(uint32_t addr, uint32_t v) { asm volatile("st.shared.u32 [%0], %1;" ::"r"(addr), "r"(v) : "memory"); }
__device__ __forceinline__ uint32_t fma_bf2(uint32_t a, uint32_t b, uint32_t c) { uint32_t r; asm("fma.rn.bf16x2 %0, %1, %2, %3;" : "=r"(r) : "r"(a), "r"(b), "r"(c)); return r; }
__device__ __forceinline__ unsigned ld_relaxed(const unsigned* p) { unsigned v; asm volatile("ld.relaxed.gpu.global.u32 %0, [%1];" : "=r"(v) : "l"(p) : "memory"); return v; }
__device__ __forceinline__ void st_relaxed(unsigned* p, unsigned v) { asm volatile("st.relaxed.gpu.global.u32 [%0], %1;" ::"l"(p), "r"(v) : "memory"); }
__device__ __forceinline__ uint4 ld_relaxed4(const void* p) {
  uint4 v; asm volatile("ld.relaxed.gpu.global.v4.u32 {%0, %1, %2, %3}, [%4];" : "=r"(v.x), "=r"(v.y), "=r"(v.z), "=r"(v.w) : "l"(p) : "memory"); return v;
}
__device__ __forceinline__ float4 ld_relaxed_f4(const void* p) {
  float4 v; asm volatile("ld.relaxed.gpu.global.v4.f32 {%0, %1, %2, %3}, [%4];" : "=f"(v.x), "=f"(v.y), "=f"(v.z), "=f"(v.w) : "l"(p) : "memory"); return v;
}
__device__ __forceinline__ void red_add4(void* p, float a, float b, float c, float d) {
  asm volatile("red.relaxed.gpu.global.add.v4.f32 [%0], {%1, %2, %3, %4};" ::"l"(p), "f"(a), "f"(b), "f"(c), "f"(d) : "memory");
}
__device__ __forceinline__ void red_add(unsigned* p, unsigned v) { asm volatile("red.relaxed.gpu.global.add.u32 [%0], %1;" ::"l"(p), "r"(v) : "memory"); }
__device__ __forceinline__ void wait_counter(const unsigned* p, unsigned target) {
  while (ld_relaxed(p) < target) __nanosleep(32);
  fence_acquire();
}
__device__ __forceinline__ float rcp(float v) { float r; asm("rcp.approx.ftz.f32 %0, %1;" : "=f"(r) : "f"(v)); return r; }
__device__ __forceinline__ float sigmoidf_(float v) { return rcp(1.f + __expf(-v)); }
__device__ __forceinline__ uint32_t phi2(float a, float b, float l2e = 1.4426950408889634f) {
  float ea, eb;
  asm("ex2.approx.ftz.f32 %0, %1;" : "=f"(ea) : "f"(a * l2e));
  asm("ex2.approx.ftz.f32 %0, %1;" : "=f"(eb) : "f"(b * l2e));
  uint32_t t = pack2(a, b), e = pack2(ea, eb), r;
  asm("max.NaN.bf16x2 %0, %0, %1;" : "+r"(t) : "r"(0x35863586u));
  asm("min.bf16x2 %0, %0, %1;" : "+r"(e) : "r"(0x3F803F80u));
  asm("add.rn.bf16x2 %0, %1, %2;" : "=r"(r) : "r"(t), "r"(e));
  return r;
}
__device__ __forceinline__ uint32_t mkdesc(uint32_t addr, uint32_t lbo) { return ((addr & 0x3FFFF) >> 4) | ((lbo >> 4) << 16); }

__device__ __forceinline__ void mma_qkv(float (&d)[96], uint32_t da, uint32_t db, int sc) {
  asm volatile("{\n.reg .pred p;\n.reg .b64 da, db;\nmov.b64 da, {%96, 0x40000040};\nmov.b64 db, {%97, 0x40000040};\nsetp.ne.b32 p, %98, 0;\n"
    "wgmma.mma_async.sync.aligned.m64n192k16.f32.bf16.bf16 "
    "{%0,%1,%2,%3,%4,%5,%6,%7,%8,%9,%10,%11,%12,%13,%14,%15,%16,%17,%18,%19,%20,%21,%22,%23,"
    "%24,%25,%26,%27,%28,%29,%30,%31,%32,%33,%34,%35,%36,%37,%38,%39,%40,%41,%42,%43,%44,%45,%46,%47,"
    "%48,%49,%50,%51,%52,%53,%54,%55,%56,%57,%58,%59,%60,%61,%62,%63,%64,%65,%66,%67,%68,%69,%70,%71,"
    "%72,%73,%74,%75,%76,%77,%78,%79,%80,%81,%82,%83,%84,%85,%86,%87,%88,%89,%90,%91,%92,%93,%94,%95}, "
    "da, db, p, 1, 1, 0, 1;\n}\n"
    : "+f"(d[0]), "+f"(d[1]), "+f"(d[2]), "+f"(d[3]), "+f"(d[4]), "+f"(d[5]), "+f"(d[6]), "+f"(d[7]),
      "+f"(d[8]), "+f"(d[9]), "+f"(d[10]), "+f"(d[11]), "+f"(d[12]), "+f"(d[13]), "+f"(d[14]), "+f"(d[15]),
      "+f"(d[16]), "+f"(d[17]), "+f"(d[18]), "+f"(d[19]), "+f"(d[20]), "+f"(d[21]), "+f"(d[22]), "+f"(d[23]),
      "+f"(d[24]), "+f"(d[25]), "+f"(d[26]), "+f"(d[27]), "+f"(d[28]), "+f"(d[29]), "+f"(d[30]), "+f"(d[31]),
      "+f"(d[32]), "+f"(d[33]), "+f"(d[34]), "+f"(d[35]), "+f"(d[36]), "+f"(d[37]), "+f"(d[38]), "+f"(d[39]),
      "+f"(d[40]), "+f"(d[41]), "+f"(d[42]), "+f"(d[43]), "+f"(d[44]), "+f"(d[45]), "+f"(d[46]), "+f"(d[47]),
      "+f"(d[48]), "+f"(d[49]), "+f"(d[50]), "+f"(d[51]), "+f"(d[52]), "+f"(d[53]), "+f"(d[54]), "+f"(d[55]),
      "+f"(d[56]), "+f"(d[57]), "+f"(d[58]), "+f"(d[59]), "+f"(d[60]), "+f"(d[61]), "+f"(d[62]), "+f"(d[63]),
      "+f"(d[64]), "+f"(d[65]), "+f"(d[66]), "+f"(d[67]), "+f"(d[68]), "+f"(d[69]), "+f"(d[70]), "+f"(d[71]),
      "+f"(d[72]), "+f"(d[73]), "+f"(d[74]), "+f"(d[75]), "+f"(d[76]), "+f"(d[77]), "+f"(d[78]), "+f"(d[79]),
      "+f"(d[80]), "+f"(d[81]), "+f"(d[82]), "+f"(d[83]), "+f"(d[84]), "+f"(d[85]), "+f"(d[86]), "+f"(d[87]),
      "+f"(d[88]), "+f"(d[89]), "+f"(d[90]), "+f"(d[91]), "+f"(d[92]), "+f"(d[93]), "+f"(d[94]), "+f"(d[95])
    : "r"(da), "r"(db), "r"(sc));
}

__device__ __forceinline__ void mma_out(float (&d)[64], uint32_t da, uint32_t db, int sc) {
  asm volatile("{\n.reg .pred p;\n.reg .b64 da, db;\nmov.b64 da, {%64, 0x40000040};\nmov.b64 db, {%65, 0x40000040};\nsetp.ne.b32 p, %66, 0;\n"
    "wgmma.mma_async.sync.aligned.m64n128k16.f32.bf16.bf16 "
    "{%0,%1,%2,%3,%4,%5,%6,%7,%8,%9,%10,%11,%12,%13,%14,%15,%16,%17,%18,%19,%20,%21,%22,%23,"
    "%24,%25,%26,%27,%28,%29,%30,%31,%32,%33,%34,%35,%36,%37,%38,%39,%40,%41,%42,%43,%44,%45,%46,%47,"
    "%48,%49,%50,%51,%52,%53,%54,%55,%56,%57,%58,%59,%60,%61,%62,%63}, "
    "da, db, p, 1, 1, 0, 1;\n}\n"
    : "+f"(d[0]), "+f"(d[1]), "+f"(d[2]), "+f"(d[3]), "+f"(d[4]), "+f"(d[5]), "+f"(d[6]), "+f"(d[7]),
      "+f"(d[8]), "+f"(d[9]), "+f"(d[10]), "+f"(d[11]), "+f"(d[12]), "+f"(d[13]), "+f"(d[14]), "+f"(d[15]),
      "+f"(d[16]), "+f"(d[17]), "+f"(d[18]), "+f"(d[19]), "+f"(d[20]), "+f"(d[21]), "+f"(d[22]), "+f"(d[23]),
      "+f"(d[24]), "+f"(d[25]), "+f"(d[26]), "+f"(d[27]), "+f"(d[28]), "+f"(d[29]), "+f"(d[30]), "+f"(d[31]),
      "+f"(d[32]), "+f"(d[33]), "+f"(d[34]), "+f"(d[35]), "+f"(d[36]), "+f"(d[37]), "+f"(d[38]), "+f"(d[39]),
      "+f"(d[40]), "+f"(d[41]), "+f"(d[42]), "+f"(d[43]), "+f"(d[44]), "+f"(d[45]), "+f"(d[46]), "+f"(d[47]),
      "+f"(d[48]), "+f"(d[49]), "+f"(d[50]), "+f"(d[51]), "+f"(d[52]), "+f"(d[53]), "+f"(d[54]), "+f"(d[55]),
      "+f"(d[56]), "+f"(d[57]), "+f"(d[58]), "+f"(d[59]), "+f"(d[60]), "+f"(d[61]), "+f"(d[62]), "+f"(d[63])
    : "r"(da), "r"(db), "r"(sc));
}

__device__ __forceinline__ void mma_ktv(float (&d)[36], uint32_t da, uint32_t db, int sc) {
  asm volatile("{\n.reg .pred p;\n.reg .b64 da, db;\nmov.b64 da, {%36, 0x40000040};\nmov.b64 db, {%37, 0x40000040};\nsetp.ne.b32 p, %38, 0;\n"
    "wgmma.mma_async.sync.aligned.m64n72k16.f32.bf16.bf16 "
    "{%0,%1,%2,%3,%4,%5,%6,%7,%8,%9,%10,%11,%12,%13,%14,%15,%16,%17,%18,%19,%20,%21,%22,%23,"
    "%24,%25,%26,%27,%28,%29,%30,%31,%32,%33,%34,%35}, "
    "da, db, p, 1, 1, 1, 1;\n}\n"
    : "+f"(d[0]), "+f"(d[1]), "+f"(d[2]), "+f"(d[3]), "+f"(d[4]), "+f"(d[5]), "+f"(d[6]), "+f"(d[7]),
      "+f"(d[8]), "+f"(d[9]), "+f"(d[10]), "+f"(d[11]), "+f"(d[12]), "+f"(d[13]), "+f"(d[14]), "+f"(d[15]),
      "+f"(d[16]), "+f"(d[17]), "+f"(d[18]), "+f"(d[19]), "+f"(d[20]), "+f"(d[21]), "+f"(d[22]), "+f"(d[23]),
      "+f"(d[24]), "+f"(d[25]), "+f"(d[26]), "+f"(d[27]), "+f"(d[28]), "+f"(d[29]), "+f"(d[30]), "+f"(d[31]),
      "+f"(d[32]), "+f"(d[33]), "+f"(d[34]), "+f"(d[35])
    : "r"(da), "r"(db), "r"(sc));
}

__device__ __forceinline__ void mma_qkvz(float (&d)[20], const uint32_t (&a)[4], uint32_t db, int sc) {
  asm volatile("{\n.reg .pred p;\n.reg .b64 db;\nmov.b64 db, {%24, 0x20};\nsetp.ne.b32 p, %25, 0;\n"
    "wgmma.mma_async.sync.aligned.m64n40k16.f32.bf16.bf16 "
    "{%0,%1,%2,%3,%4,%5,%6,%7,%8,%9,%10,%11,%12,%13,%14,%15,%16,%17,%18,%19}, "
    "{%20,%21,%22,%23}, db, p, 1, 1, 1;\n}\n"
    : "+f"(d[0]), "+f"(d[1]), "+f"(d[2]), "+f"(d[3]), "+f"(d[4]), "+f"(d[5]), "+f"(d[6]), "+f"(d[7]),
      "+f"(d[8]), "+f"(d[9]), "+f"(d[10]), "+f"(d[11]), "+f"(d[12]), "+f"(d[13]), "+f"(d[14]), "+f"(d[15]),
      "+f"(d[16]), "+f"(d[17]), "+f"(d[18]), "+f"(d[19])
    : "r"(a[0]), "r"(a[1]), "r"(a[2]), "r"(a[3]), "r"(db), "r"(sc));
}

struct Params {
  CUtensorMap x, w, xr, wo, out, gate, up, down;
};

__device__ __forceinline__ void fma8(float (&acc)[8], const uint4& w, float m) {
  acc[0] = fmaf(bf_lo(w.x), m, acc[0]); acc[1] = fmaf(bf_hi(w.x), m, acc[1]);
  acc[2] = fmaf(bf_lo(w.y), m, acc[2]); acc[3] = fmaf(bf_hi(w.y), m, acc[3]);
  acc[4] = fmaf(bf_lo(w.z), m, acc[4]); acc[5] = fmaf(bf_hi(w.z), m, acc[5]);
  acc[6] = fmaf(bf_lo(w.w), m, acc[6]); acc[7] = fmaf(bf_hi(w.w), m, acc[7]);
}
__device__ __forceinline__ float butterfly8(float (&s)[8], int lane, int o) {
#pragma unroll
  for (int k = 1; k < 8; k <<= 1) {
    const bool up = lane & (o * k);
#pragma unroll
    for (int j = 0; j < 4 / k; j++) s[j] = (up ? s[2 * j + 1] : s[2 * j]) + __shfl_xor_sync(~0u, up ? s[2 * j] : s[2 * j + 1], o * k);
  }
  return s[0];
}
constexpr int PEER = 9;
constexpr __host__ __device__ uint32_t step_list() {
  uint32_t r = 0;
  for (int j = PEER - 1; j >= 0; j--) if (j != OWN) r = r << 4 | j % 5 | (j < 5) << 3;
  return r;
}
template <bool BY_SM> struct Tile {
  int sm, tm, tn, mu;
  bool spare;
  __device__ __forceinline__ Tile() {
    if (BY_SM) asm volatile("mov.u32 %0, %%smid;" : "=r"(sm));
    else sm = blockIdx.x + (blockIdx.x >= 120) * 4;
    const int tp = sm >> 1, pr = sm & 1;
    const int v = tp < 32 ? tp : tp < 60 ? (tp * 293 - 928) >> 8 : tp * 8 - 464, g = v & 7, i = v >> 3;
    const int j = i * 11 >> 5, c = i - j * 3;
    tm = (v & 6) * 2 + (c < 2 ? j : 3); tn = (v & 1) * 4 + (c < 2 ? c : j) * 2 + pr;
    mu = i == NOMOD ? 112 : g * 14 + (i - (i > NOMOD)) * 2 + pr;
    spare = (tp | 1) == 61;
  }
};

template <bool BY_SM> __global__ void __cluster_dims__(2, 1, 1) __launch_bounds__(NTHREADS, 1) fused_kernel(const __nv_bfloat16* __restrict__ px, Scratch* gs, const __nv_bfloat16* __restrict__ w_gate,
             const __nv_bfloat16* __restrict__ w_up, const __nv_bfloat16* __restrict__ w_r, const __nv_bfloat16* __restrict__ gate_w,
             const __grid_constant__ Params p, void* pout) {
  extern __shared__ __align__(1024) uint8_t smem[];
  const uint32_t sb = __shfl_sync(~0u, (uint32_t)__cvta_generic_to_shared(smem), 0);
  const int tid = threadIdx.x, lane = tid & 31;
  const int warp = __shfl_sync(~0u, tid >> 5, 0), wg = warp >> 2;
  const uint32_t t_start = clock32();
  const Tile<BY_SM> tile;
  const int tm = tile.tm, tn = tile.tn, mu = tile.mu, cta = tm * 8 + tn;
  {
    const uint32_t cnt = (uint32_t)((warp & 8 ? bar_counts(16) : bar_counts(0)) >> (warp & 7) * 8);
    if (elect()) mbar_init(sb + OFF_BAR + warp * 16, cnt & 15);
    if (elect()) mbar_init(sb + OFF_BAR + warp * 16 + 8, cnt >> 4 & 15);
    if (elect()) mbar_init(sb + BAR_LAND + warp * 8, 1);
    asm volatile("fence.mbarrier_init.release.cluster;" ::: "memory");
  }
  if (warp == 0 && !tile.spare) {
#pragma unroll
    for (int s = 0; s < PRE; s++) {
      if (elect()) tma3d(sb + OFF_RING + s * STAGE_BYTES + A_BYTES, &p.w, tn * 64, s * 64, 0, sb + BAR_FULL + s * 8);
      if (elect()) tma2d(sb + OFF_RING + s * STAGE_BYTES, &p.x, s * 64, tm * 128, sb + BAR_FULL + s * 8);
      PROF_P(lane == 0, 64 + s);
    }
    if (elect()) {
#pragma unroll
      for (int s = 0; s < PRE; s++) { mbar_expect_tx(sb + BAR_FULL + s * 8, STAGE_BYTES); mbar_arrive(sb + BAR_FULL + s * 8); }
    }
  }
  asm volatile("" ::: "memory");
  if (warp == 5) {
#pragma unroll
    for (int i = 0; i < 4; i++) sts128(sb + OFF_ONES + i * 512 + lane * 16, 0x3F803F80u, 0x3F803F80u, 0x3F803F80u, 0x3F803F80u);
    sts32(sb + OFF_MISC + 20, 0x3FB8AA3Bu);
    fence_async_smem();
  }
  __syncthreads();
  if (tile.spare) {
    if (warp == 0) {
      const unsigned tag = (ld_relaxed(&gs->spare[tile.sm & 3]) + 1) & 0xFFF;
      const unsigned long long t0 = gtime();
      uint4 r4;
      do {
        __nanosleep(2048);
        if (gtime() - t0 > WATCHDOG_NS) __trap();
        r4 = ld_relaxed4(&gs->rslot[tile.sm & 3][lane * 4]);
      } while (!__all_sync(~0u, (((r4.x ^ tag) | (r4.y ^ tag) | (r4.z ^ tag) | (r4.w ^ tag)) & 0xFFF) == 0));
      if (tid == 0) st_relaxed(&gs->spare[tile.sm & 3], tag);
    }
    return;
  }

  if (wg == 3) {
    asm volatile("setmaxnreg.dec.sync.aligned.u32 24;");
    if (warp == 12) {
      mbar_wait(sb + BAR_W31, 0);
      mbar_wait(sb + BAR_IDX, 0);
      const uint32_t lowb = (1u << (tn & 6) * 4) - 1;
      uint32_t slabs = 0x76543210u, steps = step_list();
      const uint4* src = gs->o[tm][0];
      unsigned seen = 0;
#pragma unroll 1
      for (int n = 8; n >= 6; n -= 2) {
#pragma unroll 1
        for (int i = 0; i < n; i++, slabs >>= 4, steps >>= 4) {
          const uint32_t s = steps & 7, full = sb + BAR_FULL + s * 8, need = 4u << (slabs & 7) * 4;
          const uint32_t land = n == 8 ? full : sb + BAR_LAND + i * 8;
          mbar_wait(full + (BAR_EMPTY - BAR_FULL), steps >> 3 & 1);
          PROF(lane == 0 && (!PROFC || n == 6), 224 + i + (n == 6) * 10);
          if (!__all_sync(~0u, seen & need)) {
            while (!__all_sync(~0u, (seen = ld_relaxed(gs->cnt[tm])) & need)) __nanosleep(FSL);
          }
          if (elect()) bulk_load(sb + OFF_RING + s * O_BYTES, src + (slabs & 7) * 1024, A_BYTES, land);
          if (elect()) mbar_expect_tx(land, A_BYTES);
          PROF(lane == 0 && (!PROFC || n == 6), 240 + i + (n == 6) * 10);
        }
        slabs = (0x76543210u & lowb) | (0x765432u & ~lowb);
        steps = 0x0CBA98u;
        src += 8 * 1024;
      }
    } else if (warp == 13) {
      uint32_t full = sb + BAR_FULL + PRE * 8, dst = sb + OFF_RING + PRE * STAGE_BYTES + A_BYTES, c0 = tn * 64, c1 = PRE * 64;
#pragma unroll 1
      for (int g = PRE; g < 32; g++) {
        if (g < 4) while ((int)(clock32() - t_start) < g * ST1) {}
        const bool reuse = (g >> 2) == 4;
        mbar_wait(full + (BAR_EMPTY - BAR_FULL), ((g >> 2) & 1) ^ 1);
        if (!reuse && elect()) tma2d(dst - A_BYTES, &p.x, c1, tm * 128, full);
        if (elect()) tma3d(dst, &p.w, c0, c1, 0, full);
        if (elect()) { mbar_expect_tx(full, reuse ? BQ_BYTES : STAGE_BYTES); mbar_arrive(full); }

        PROF_P(lane == 0, 64 + g);
        const uint32_t i = g - RT_G0;
        if (i < 4 && elect()) {
          mbar_expect_tx(sb + BAR_RT + i * 8, i ? 8192 : 8192 + 4096);
          tma2d(sb + OFF_PK + i * 8192, &p.xr, ((i + RT_ROT) & 3) * 256, cta * 16, sb + BAR_RT + i * 8);
          if (i == 0) { bulk_load(sb + OFF_KVB, w_r, 2048, sb + BAR_RT); bulk_load(sb + OFF_KVB + 2048, gate_w, 2048, sb + BAR_RT); }
        }
        const uint32_t c = g - MOD_START;
        if (c == MOD_BUFS) mbar_wait(sb + BAR_RTD, 0);
        if (c < MOD_BUFS0 && mu < MOD_CTAS && elect()) {
          PROF_P(true, 192 + c);
          const uint32_t mfull = sb + BAR_MFULL + c * 8, mdst = sb + OFF_MOD + c * 8192;
          mbar_expect_tx(mfull, c ? 8192 : 8192 + 2048);
          tma3d(mdst, &p.gate, mu * 32, c * 16, 0, mfull); tma3d(mdst + 4096, &p.up, mu * 32, c * 16, 0, mfull);
        }
        const uint32_t pc = g - PF_MOD;
        if (pc < 16 && elect()) bulk_prefetch((cta & 64 ? w_up : w_gate) + (size_t)(pc * 64 + (cta & 63)) * F_, F_ * 2);
        full += 8; dst += STAGE_BYTES; c1 += 64;
        if ((g & 3) == 3) { full -= 32; dst -= 4 * STAGE_BYTES; }
        if (g == 15) { c0 += 512; c1 = 768; }
        if (g == 19) c1 = 0;
      }
      mbar_arrive_warp(sb + BAR_W31);
      const uint32_t lowb = (1u << (tn & 6) * 4) - 1;
      uint64_t slabs = (uint64_t)((0xFEDCBA98u & lowb) | (0xFEDCBAu & ~lowb)) << 40 | (uint64_t)(8 + (tn ^ 1)) << 36 | (uint64_t)(8 + tn) << OWN * 4 |
                       (0x76543210ull & ~(~0ull << OWN * 4)) | (0x765432100ull & ~0ull << (OWN * 4 + 4));
      uint32_t ph = 1;
      c1 = 0;
#pragma unroll 1
      for (int g = 0; g < 16; g++) {
        mbar_wait(full + (BAR_EMPTY - BAR_FULL), ph);
        if (elect()) tma3d(dst, &p.wo, 0, c1, tn * 2, full);
        if (elect()) mbar_expect_tx(full, BO_BYTES);
        PROF_P(lane == 0, 96 + g);
        if (g == OWN && elect()) mbar_arrive(full);
        full += 8; dst += O_BYTES; slabs >>= 4; c1 = ((uint32_t)slabs & 15) * 64;
        if (full == sb + BAR_EMPTY) { full -= 40; dst -= 5 * O_BYTES; ph ^= 1; }
      }
    } else if (warp == 14) {
      if (mu < MOD_CTAS) {
        uint32_t full = sb + BAR_MFULL, dst = sb + OFF_MOD, ph = 0;
#pragma unroll 1
        for (int c = MOD_BUFS0; c < 24; c++) {
          mbar_wait(full + (BAR_MEMPTY - BAR_MFULL), ph);
          PROF_P(lane == 0, 192 + c);
          if (c < 16) {
            if (elect()) { tma3d(dst, &p.gate, mu * 32, c * 16, 0, full); tma3d(dst + 4096, &p.up, mu * 32, c * 16, 0, full); }
          } else if (elect()) tma3d(dst, &p.down, 0, mu * 32 + (c - 16) * 4, 0, full);
          if (elect()) mbar_expect_tx(full, 8192);
          full += 8; dst += 8192;
          if (dst == sb + OFF_PK) { full -= MOD_BUFS * 8; dst = sb + OFF_MOD; ph ^= 1; }
        }
      }
      if (elect()) {
      mbar_wait(sb + BAR_IDX, 0);
      const bool paired = lds32(sb + OFF_MISC + 28) < 0x200;
      const uint32_t pb = peer_addr(sb);
      mbar_wait(sb + BAR_EMPTY + PEER % 5 * 8, 0);
      mbar_expect_tx(sb + BAR_FULL + PEER % 5 * 8, A_BYTES);
      if (paired) mbar_arrive_peer(pb + BAR_PA);
      mbar_wait(sb + BAR_OST, 0);
      mbar_expect_tx(sb + BAR_X, 32768);
      tma2d(sb + OFF_PK, &p.x, tn * 128, tm * 128, sb + BAR_X);
      tma2d(sb + OFF_V, &p.x, tn * 128 + 64, tm * 128, sb + BAR_X);
      if (paired) {
        mbar_wait(sb + BAR_PA, 0);
        mbar_wait(sb + BAR_OWN, 0);
        bulk_push(pb + OFF_RING + PEER % 5 * O_BYTES, sb + OFF_MOD, A_BYTES, pb + BAR_FULL + PEER % 5 * 8);
        mbar_wait(sb + BAR_EMPTY + PEER % 5 * 8, 1);
        mbar_arrive_peer(pb + BAR_PA);
        mbar_wait(sb + BAR_PA, 1);
      } else {
        mbar_wait(sb + BAR_OWN, 0);
        __nanosleep(500);
        bulk_load(sb + OFF_RING + PEER % 5 * O_BYTES, gs->o[tm][8 + (tn ^ 1)], A_BYTES, sb + BAR_FULL + PEER % 5 * 8);
      }
      }
    } else if (elect()) {
#pragma unroll 1
      for (int i = 2; i < 8; i++) asm volatile("prefetch.tensormap [%0];" ::"l"(&p.x + i) : "memory");
      mbar_wait_bounded(sb + BAR_DONE, 0);
    }
  } else if (wg == 2) {
    asm volatile("setmaxnreg.dec.sync.aligned.u32 40;");
    const int mw = warp & 3;
    if (mw == 0) {
      const unsigned tag = (ld_relaxed(&gs->rslot[tn][cta]) + 1) & 0xFFF;
#pragma unroll
      for (int i = 0; i < 4; i++)
        if (lane < NCLR) ((float4*)gs)[cta * (NCLR * 4) + i * NCLR + lane] = make_float4(0.f, 0.f, 0.f, 0.f);
      if (lane == 29) st_relaxed(&gs->block[cta], blockIdx.x << 12 | tag);
      fence_release();
      nb_sync(NB_KEY, 160);
      const uint4 k4 = lds128(sb + OFF_MISC);
      if (lane < 8) st_relaxed(&gs->rslot[lane][cta], max(max(k4.x, k4.y), max(k4.z, k4.w)) | tag);
      if (lane < 16) st_relaxed(&gs->gslot[cta * 16 + lane], lds32(sb + OFF_G + lane * 4) | tag);
      PROF(lane == 0, 20);
      uint4 r4;
      do {
        __nanosleep(RT_SLEEP);
        r4 = ld_relaxed4(&gs->rslot[tn][lane * 4]);
      } while (!__all_sync(~0u, (((r4.x ^ tag) | (r4.y ^ tag) | (r4.z ^ tag) | (r4.w ^ tag)) & 0xFFF) == 0));
      const int c0 = 0xFFF0 - lane * 64;
      unsigned key = max(max((r4.x & 0xFFFF0000u) | (c0 + ((r4.x >> 12) & 15)), (r4.y & 0xFFFF0000u) | (c0 - 16 + ((r4.y >> 12) & 15))),
                         max((r4.z & 0xFFFF0000u) | (c0 - 32 + ((r4.z >> 12) & 15)), (r4.w & 0xFFFF0000u) | (c0 - 48 + ((r4.w >> 12) & 15))));
      key = __reduce_max_sync(~0u, key);
      if (elect()) {
        sts32(sb + OFF_MISC + 16, key);
        sts32(sb + OFF_MISC + 24, tag & 1);
        if (mu < MOD_CTAS) bulk_load(sb + OFF_XSEL, px + (size_t)(0xFFFF - (key & 0xFFFF)) * D_, 2048, sb + BAR_MFULL);
      }
      PROF(lane == 0, 21);
      unsigned nb;
      do {
        r4 = ld_relaxed4(&gs->gslot[tm * 128 + lane * 4]);
        nb = ld_relaxed(&gs->block[cta ^ 1]);
      } while (!__all_sync(~0u, (((r4.x ^ tag) | (r4.y ^ tag) | (r4.z ^ tag) | (r4.w ^ tag) | (nb ^ tag)) & 0xFFF) == 0));
      sts128(sb + OFF_G + lane * 16, r4.x & 0xFFFF0000u, r4.y & 0xFFFF0000u, r4.z & 0xFFFF0000u, r4.w & 0xFFFF0000u);
      sts32(sb + OFF_MISC + 28, (PAIRED && nb >> 12 == (blockIdx.x ^ 1) ? 0x1FF : 0x3FF) & ~((1 << PC) - 1 | 1 << OWN));
      fence_acquire();
      __syncwarp();
      mbar_arrive_warp(sb + BAR_IDX);
    }
    PROF(tid == 256, 22);
    if (mu >= MOD_CTAS) {
      mbar_arrive_warp(sb + BAR_IDX);
      mbar_arrive_warp(sb + BAR_OA);
    } else {
      const uint32_t wp = sb + OFF_MOD + (mw >> 1) * 4096 + (mw & 1) * 512 + lane * 16;
      uint32_t mp = sb + OFF_XSEL - 128 + (mw & 1) * 64 + (lane >> 2) * 8, mc = 128;
      float acc[8] = {0.f, 0.f, 0.f, 0.f, 0.f, 0.f, 0.f, 0.f};
      uint32_t b = ~0u, ph = 0, a = sb + OFF_ONES - 3072;
      float m3 = 0.f;
      const uint32_t zero = lds32(sb + OFF_ONES) & 1;
      uint2 m = make_uint2(0, 0);
      uint4 w0 = make_uint4(0, 0, 0, 0), w1 = w0, w2 = w0, w3 = w0;
#pragma unroll 1
      for (int c = -1;; c++) {
        fma8(acc, w3, m3);
        w3 = lds128(a + 3072);
        const uint32_t rel = sb + BAR_MEMPTY + b * 8;
        if (c == 16) {
          const uint32_t ft = fresh_tid(), fl = ft & 31;
          sts32(sb + OFF_PART + (ft & 96) * 4 + ((ft & 3) * 8 + (fl >> 2)) * 4, __float_as_uint(butterfly8(acc, fl, 4)));
          nb_sync(NB_MODW, 128);
          const float* part = (const float*)(smem + OFF_PART) + fl;
          const float gp = bf_round(part[0] + part[32]), up = bf_round(part[64] + part[96]);
          *(__nv_bfloat16*)(smem + OFF_PART + 512 + fl * 2) = __float2bfloat16_rn(bf_round(gp * sigmoidf_(gp)) * up);
          __syncwarp();
          mp = sb + OFF_PART + 512; mc = 8;
          m = lds64(mp);
#pragma unroll
          for (int i = 0; i < 8; i++) acc[i] = 0.f;
          PROF(lane == 0 && mw == 0, 23);
        }
        if (++b == (c < MOD_BUFS0 ? MOD_BUFS0 : MOD_BUFS)) { b = 0; ph ^= 1; }
        const uint32_t ok = mbar_test(sb + BAR_MFULL + b * 8, ph);
        fma8(acc, w0, bf_lo(m.x));
        if (c >= 0) mbar_arrive_warp(rel + ((w3.x | __float_as_uint(acc[7])) & zero));
        fma8(acc, w1, bf_hi(m.x));
        fma8(acc, w2, bf_lo(m.y));
        m3 = bf_hi(m.y);
        if (c == 23) break;
        if (!ok) mbar_wait(sb + BAR_MFULL + b * 8, ph);
        a = wp + b * 8192;
        mp += mc;
        m = lds64(mp);
        w0 = lds128(a); w1 = lds128(a + 1024); w2 = lds128(a + 2048);
      }
      fma8(acc, w3, m3);
      mbar_arrive_warp(sb + BAR_OA);
      float* yacc = gs->y[tn] + (fresh_tid() & 127) * 8;
      red_add4(yacc, acc[0], acc[1], acc[2], acc[3]);
      red_add4(yacc + 4, acc[4], acc[5], acc[6], acc[7]);
      PROF(lane == 0 && mw == 0, 25);
      nb_sync(NB_MODW, 128);
      if (mw == 0 && elect()) { fence_release(); red_add(gs->cnt[32], 1); }
      PROF(lane == 0 && mw == 0, 24);
    }
    const unsigned key = lds32(sb + OFF_MISC + 16);
    const int sel = 0xFFFF - (int)(key & 0xFFFF) - tm * 128;
    if (mw == 0 && sel >= 0 && sel < 128) {
      if (elect()) wait_counter(gs->cnt[32], MOD_CTAS);
      __syncwarp();
      const unsigned k16 = key >> 16;
      const float rs = bf_round(sigmoidf_(__uint_as_float(((k16 & 0x8000u) ? (k16 & 0x7FFFu) : (~k16 & 0xFFFFu)) << 16)));
      float4 v = make_float4(0.f, 0.f, 0.f, 0.f);
#pragma unroll 4
      for (int i = 0; i < 8; i++) {
        const float4 u = ld_relaxed_f4(gs->y[i] + tn * 128 + lane * 4);
        v.x += u.x; v.y += u.y; v.z += u.z; v.w += u.w;
      }
      mbar_wait(sb + BAR_X, 0);
      uint2* xp = (uint2*)(smem + OFF_PK + (lane >> 4) * 16384 + sel * 128 + ((((lane >> 1) & 7) ^ (sel & 7)) << 4) + (lane & 1) * 8);
      const uint2 xv = *xp;
      *xp = make_uint2(pack2(bf_lo(xv.x) + bf_round(bf_round(v.x) * rs), bf_hi(xv.x) + bf_round(bf_round(v.y) * rs)),
                       pack2(bf_lo(xv.y) + bf_round(bf_round(v.z) * rs), bf_hi(xv.y) + bf_round(bf_round(v.w) * rs)));
      __syncwarp();
      mbar_arrive_warp(sb + BAR_Y);
    }
  } else {
    asm volatile("setmaxnreg.inc.sync.aligned.u32 224;");
    const int w = warp & 3, wt = tid & 127;
    const int nb_self = NB_WG0 + wg;
    const uint32_t da0 = mkdesc(sb + OFF_RING, 16), db0 = mkdesc(sb + OFF_RING + A_BYTES, 8192);

    if (wg == 1) {
      float s[8] = {0.f, 0.f, 0.f, 0.f, 0.f, 0.f, 0.f, 0.f};
      const uint32_t zero = lds32(sb + OFF_ONES) & 1;
      uint32_t mask = 0xffff0000u;
#pragma unroll 1
      for (int i = 0; i < 4; i++) {
        const uint32_t u = (i + RT_ROT) & 3;
        mbar_wait(sb + BAR_RT + i * 8, 0);
        const uint4 wr = lds128(sb + OFF_KVB + u * 512 + lane * 16), gw = lds128(sb + OFF_KVB + 2048 + u * 512 + lane * 16);
        uint4 xv[4];
#pragma unroll
        for (int r = 0; r < 4; r++) xv[r] = lds128(sb + OFF_PK + i * 8192 + (w * 4 + r) * 512 + lane * 16);
        const float wf[16] = {bf_lo(wr.x), bf_hi(wr.x), bf_lo(wr.y), bf_hi(wr.y), bf_lo(wr.z), bf_hi(wr.z), bf_lo(wr.w), bf_hi(wr.w),
                              bf_lo(gw.x), bf_hi(gw.x), bf_lo(gw.y), bf_hi(gw.y), bf_lo(gw.z), bf_hi(gw.z), bf_lo(gw.w), bf_hi(gw.w)};
#pragma unroll
        for (int r = 0; r < 4; r++) {
          const uint4 xq = xv[r];
          const float xf[8] = {bf_lo(xq.x), __uint_as_float(xq.x & mask), bf_lo(xq.y), bf_hi(xq.y), bf_lo(xq.z), bf_hi(xq.z), bf_lo(xq.w), bf_hi(xq.w)};
#pragma unroll
          for (int j = 0; j < 8; j++) { s[2 * r] = fmaf(xf[j ^ 1], wf[j ^ 1], s[2 * r]); s[2 * r + 1] = fmaf(xf[j ^ 1], wf[8 + (j ^ 1)], s[2 * r + 1]); }
          mask = ((__float_as_uint(s[2 * r]) | __float_as_uint(s[2 * r + 1])) & zero) | 0xffff0000u;
        }
      }
      mbar_arrive_warp(sb + BAR_RTD);
      float v = butterfly8(s, lane, 1);
      PROF_C(wt == 0 && v != 12345.f, 19);
      v += __shfl_xor_sync(~0u, v, 8);
      v = bf_round(v + __shfl_xor_sync(~0u, v, 16));
      const unsigned rb = __float_as_uint(v) >> 16, row = w * 4 + ((lane & 7) >> 1);
      unsigned key = (lane & 1) ? 0u : ((((rb & 0x8000u) ? (~rb & 0xFFFFu) : (rb | 0x8000u)) << 16) | ((15 - row) << 12));
      key = __reduce_max_sync(~0u, key);
      if (lane == 0) sts32(sb + OFF_MISC + w * 4, key);
      if (lane < 8 && (lane & 1)) sts32(sb + OFF_G + row * 4, __float_as_uint(bf_round(sigmoidf_(v))));
      nb_arrive(NB_KEY, 160);
      nb_sync(NB_ORDER_AB, 256);
    }

    uint32_t pq[2][4][4];
    float4* const kvacc = &gs->kv[wg][tn][0][wt];
    {
      float acc[2][96];
      PROF_C(wt == 0, 1 + wg * 8);
#pragma unroll 1
      for (int g = 0; g < 14; g++) {
        const uint32_t s = g & 3;
        const uint32_t da = da0 + s * (STAGE_BYTES >> 4), db = db0 + s * (STAGE_BYTES >> 4);
        mbar_wait(sb + BAR_FULL + s * 8, (g >> 2) & 1);
        PROF_C(wt == 0, 64 + wg * 16 + g);
#pragma unroll
        for (int m = 0; m < 2; m++) {
          wg_fence();
#pragma unroll
          for (int kk = 0; kk < 4; kk++) mma_qkv(acc[m], da + (m * 512 + kk * 2), db + kk * 128, kk ? 1 : g);
          wg_commit();
          if (m == 0) {
            wg_wait<1>();
            if (g) mbar_arrive_warp(sb + BAR_EMPTY + ((g + 3) & 3) * 8);
          }
        }
      }
      auto half_step = [&](int m, int g) {
        wg_fence();
#pragma unroll
        for (int kk = 0; kk < 4; kk++)
          mma_qkv(acc[m], da0 + ((g & 3) * (STAGE_BYTES >> 4) + m * 512 + kk * 2), db0 + ((g & 3) * (STAGE_BYTES >> 4) + kk * 128), 1);
        wg_commit();
      };
#pragma unroll
      for (int g = 14; g < 16; g++) {
        mbar_wait(sb + BAR_FULL + (g & 3) * 8, 1);
        PROF_C(wt == 0, 64 + wg * 16 + g);
        half_step(0, g);
        if (g == 14) { wg_wait<1>(); mbar_arrive_warp(sb + BAR_EMPTY + ((g + 3) & 3) * 8); }
      }
      half_step(1, 14);
      half_step(1, 15);
      if (wg == 0) nb_arrive(NB_ORDER_AB, 256);
      mbar_wait(sb + BAR_IDX, 0);
      if (wg == 1) nb_sync(NB_STG, 256);
      wg_wait<2>();
      PROF_C(wt == 0, 3 + wg * 8);

      const uint32_t st_row = (uint32_t)(w * 16 + (lane & 15)) * 128;
      float c[36];
      const uint32_t dk = mkdesc(sb + OFF_PK, 16), dv = mkdesc(sb + OFF_V, OFF_ONES - OFF_V);
      uint32_t l2k[8 + PA];
#pragma unroll
      for (int u = 0; u < PA; u++) l2k[u] = 0x3FB8AA3Bu;
#pragma unroll
      for (int u = 0; u < 8; u++) {
        const int m = u >> 2, j = u & 3;
        const uint32_t a = sb + m * 8192 + st_row + ((((lane >> 4) + 2 * j) ^ (lane & 7)) << 4);
        const float* k = &acc[m][32 + 8 * j];
        const float l = __uint_as_float(l2k[u]);
        if (u == M1) {
          wg_wait<1>();
          mbar_arrive_warp(sb + BAR_EMPTY + 2 * 8);
        }
        if (u == MM) {
          wg_wait<0>();
          mbar_arrive_warp(sb + BAR_EMPTY + 3 * 8);
        }
        const float* v = &acc[m][64 + 8 * j];
        stsm4(a + OFF_V, pack2(v[0], v[1]), pack2(v[2], v[3]), pack2(v[4], v[5]), pack2(v[6], v[7]));
        const uint32_t r0 = phi2(k[0], k[1], l), r1 = phi2(k[2], k[3], l), r2 = phi2(k[4], k[5], l), r3 = phi2(k[6], k[7], l);
        stsm4(a + OFF_PK, r0, r1, r2, r3);
        if (u + PA < 8) l2k[u + PA] = lds32(sb + OFF_MISC + 20);
      }
      fence_async_smem();
      nb_sync(nb_self, 128);
      PROF_C(wt == 0, 8 + wg * 8);
      wg_fence();
#pragma unroll
      for (int kk = 0; kk < 8; kk++) mma_ktv(c, dk + kk * 128, dv + (kk * 128 - (kk << 23)), kk ? 1 : 0);
      wg_commit();
      if (wg == 1) nb_arrive(NB_ORDER_BO, 256);
      auto reduce = [&](float4* dst, int gap) {
        wg_wait<0>();
        PROF_C(wt == 0, 4 + wg * 8);
        float u[18];
#pragma unroll
        for (int i = 0; i < 16; i++) u[i] = w >= 2 ? c[16 + i] : c[i];
        u[16] = __shfl_down_sync(~0u, u[15], 1);
        u[17] = lane & 2 ? c[34] : c[32];
#pragma unroll
        for (int i = 0; i < 5; i++) {
          if (gap && i) __nanosleep(gap);
          red_add4(dst + i * 128, u[3 * i], u[3 * i + 1], u[3 * i + 2], i < 3 && !(lane & 1) ? u[i == 0 ? 15 : i == 1 ? 17 : 16] : 1.f);
        }
      };
      const uint32_t zero = lds32(sb + OFF_ONES) & 1;
      if (wg) reduce(kvacc, 0);
      const float l2e = __uint_as_float(lds32(sb + OFF_MISC + 20));
      uint32_t dep = 0;
#pragma unroll
      for (int u = 0; u < 8; u++) {
#pragma unroll
        for (int i = 0; i < 4; i++) dep |= pq[u >> 2][u & 3][i] = phi2(acc[u >> 2][8 * (u & 3) + 2 * i], acc[u >> 2][8 * (u & 3) + 2 * i + 1], l2e);
      }
      float4* const kvp = kvacc + (dep & zero);
      if (!wg) reduce(kvp, RED_SLEEP);
      PROF_C(wt == 0 && kvp == kvacc, 34 + wg * 2);
      for (int tries = wg ? 0 : 9;; tries++) {
        if (tries > RETRY)
          while (ld_relaxed((const unsigned*)&(kvp - lane)[NV * 128 - 128 + 31].w) != 0x41800000u) __nanosleep(wg ? KV_SLEEP : KV_SLEEP_A);
        float4 kv[NV];
#pragma unroll
        for (int i = 0; i < NV; i++) kv[i] = ld_relaxed_f4(kvp + i * 128);
        const uint32_t kb = sb + OFF_KVB + (w >> 1) * 2560 + (w & 1) * 256;
        const uint32_t ka = kb + (lane >> 4) * 512 + (lane & 15) * 16;
        stsm4(ka, pack2(kv[0].x, kv[0].y), pack2(kv[0].z, kv[1].x), pack2(kv[1].y, kv[1].z), pack2(kv[2].x, kv[2].y));
        const uint32_t zz = pack2(kv[1].w, kv[1].w);
        if (!(lane & 1)) sts128(kb + 2048 + (lane & 2) * 64 + (lane >> 2) * 16, zz, zz, zz, zz);
        const float u15 = __shfl_up_sync(~0u, kv[2].w, 1);
        stsm4(ka + 1024, pack2(kv[2].z, kv[3].x), pack2(kv[3].y, kv[3].z), pack2(kv[4].x, kv[4].y), pack2(kv[4].z, lane & 1 ? u15 : kv[0].w));
        const bool ok = !(lane & 1) || kv[0].w + kv[1].w + kv[2].w + kv[3].w + kv[4].w == 80.f;
        if (__all_sync(~0u, ok)) { PROF_V(wg && lane == 0, 40 + w, tries * 100 + 2); break; }
      }
    }
    {
      PROF_C(wt == 0, 5 + wg * 8);
      fence_async_smem();
      nb_sync(nb_self, 128);
      float o[2][2][20];
      const uint32_t dz = mkdesc(sb + OFF_KVB, 128);
      wg_fence();
#pragma unroll
      for (int m = 0; m < 2; m++) {
#pragma unroll
        for (int h = 0; h < 2; h++)
#pragma unroll
          for (int kk = 0; kk < 2; kk++) mma_qkvz(o[m][h], pq[m][2 * h + kk], dz + (h * 160 + kk * 16), kk);
        wg_commit();
      }
      const uint32_t tmask = (lane & 3) == (lane >> 3), tbit = lds32(sb + OFF_MISC + 24) & tmask;
      float gr[2][2], sc[4];
#pragma unroll
      for (int i = 0; i < 4; i++) gr[i >> 1][i & 1] = __uint_as_float(lds32(sb + OFF_G + ((i >> 1) * 64 + (i & 1) * 8 + w * 16 + (lane >> 2)) * 4));
      if (wg == 1) {
        mbar_arrive_warp(sb + BAR_OST);
        mbar_wait(sb + BAR_OA, 0);
      }
      const uint32_t os = sb + (wg ? OFF_MOD : OFF_PK) + w * 2048;
      uint8_t* const og = (uint8_t*)gs->o[tm][wg * 8 + tn] + w * 2048;
#pragma unroll
      for (int m = 0; m < 2; m++) {
        if (m == 0) wg_wait<1>();
        if (m == 0) PROF_C(wt == 0, 6 + wg * 8);
#pragma unroll
        for (int h = 0; h < 2; h++) {
          const float* oo = o[m][h];
          uint32_t pin = 0;
          if (!m && h) {
            wg_wait<0>();
#pragma unroll
            for (int i = 0; i < 4; i++) pin |= __float_as_uint(sc[i] = gr[1][i & 1] * rcp(o[1][i >> 1][16 + (i & 1) * 2] + 1e-6f));
            pin &= __float_as_uint(gr[0][0]) & 16;
          }
          const float s0 = m ? sc[2 * h] : gr[m][0] * rcp(oo[16] + 1e-6f), s1 = m ? sc[2 * h + 1] : gr[m][1] * rcp(oo[18] + 1e-6f);
#pragma unroll
          for (int j = 0; j < 2; j++)
            stsm4(os + m * 8192 + (lane & 15) * 128 + ((((lane >> 4) + 4 * h + 2 * j) ^ (lane & 7)) << 4) + (j ? pin : 0),
                  (pack2(oo[8 * j] * s0, oo[8 * j + 1] * s0) & ~tmask) | tbit, (pack2(oo[8 * j + 2] * s1, oo[8 * j + 3] * s1) & ~tmask) | tbit,
                  pack2(oo[8 * j + 4] * s0, oo[8 * j + 5] * s0), pack2(oo[8 * j + 6] * s1, oo[8 * j + 7] * s1));
        }
        fence_async_smem();
        __syncwarp();
        if (elect()) bulk_store(og + m * 8192, os + m * 8192, 2048);
      }
      if (elect()) {
        bulk_commit();
        if (wg) mbar_arrive(sb + BAR_OWN);
        PROF(wt == 0, 7 + wg * 8);
        if (!wg) red_add(gs->cnt[tm], 1u << tn * 4);
        asm volatile("cp.async.bulk.wait_group.read 0;" ::: "memory");
        PROF(wt == 0, 17 + wg);
        PROF(wt == 96, 38 + wg);
      }
    }

    __syncwarp();
    const uint32_t par = lds32(sb + OFF_MISC + 24), cw = lane * 32 + (lane & 4) * 4 + (lane >> 3) * 4;
    auto check_tile = [&](int g, uint32_t s) {
      const uint32_t a = sb + OFF_RING + s * O_BYTES + w * 2048, fix = sb + BAR_FIX + warp * 8;
      for (;;) {
        const uint32_t u0 = lds32(a + cw), u1 = lds32(a + cw + 1024), u2 = lds32(a + cw + 8192), u3 = lds32(a + cw + 9216);
        if (__all_sync(~0u, !(mism(mism(u0, u1, par), mism(u2, u3, par), 0) & 1))) break;
        PROF_V(lane == 0, 44 + g, 102);
        const int slab = g < OWN ? g : g < PEER ? g - 1 : g == PEER ? 8 + (tn ^ 1) : g - 10 < (tn & 6) ? g - 2 : g;
        const uint4* src = gs->o[tm][slab] + w * 128;
        const uint32_t ph = !mbar_test(fix, 1);
        fence_async_smem();
        __syncwarp();
        if (elect()) { mbar_expect_tx(fix, 4096); bulk_load(a, src, 2048, fix); bulk_load(a + 8192, src + 512, 2048, fix); }
        mbar_wait(fix, ph);
      }
    };
    if (wg == 1) {
#pragma unroll 1
      for (int g = 10; g < 16; g++) {
        const uint32_t s = g == 15 ? 0 : g - 10;
        mbar_wait(sb + BAR_LAND + (g - 10) * 8, 0);
        PROF_C(wt == 0, 214 + g);
        check_tile(g, s);
        if (w) nb_arrive(NB_CHK + (g & 1), 128);
        else { nb_sync(NB_CHK + (g & 1), 128); mbar_arrive_warp(sb + BAR_FULL + s * 8); }
        if (g & 1) nb_sync(nb_self, 128);
      }
    } else {
      nb_arrive(NB_STG, 256);
      float acc[2][64];
      mbar_wait(sb + BAR_W31, 0);
#pragma unroll 1
      for (int g = 0; g < PC; g++) { mbar_wait(sb + BAR_EMPTY + g * 8, 1); mbar_wait(sb + BAR_FULL + g * 8, 0); check_tile(g, g); }
      const uint32_t chk = __shfl_sync(~0u, lds32(sb + OFF_MISC + 28), 0);
      nb_sync(NB_ORDER_BO, 256);
      PROF_C(wt == 0, 26);
      uint32_t xr[2][8][4], q[2][2];
      const uint32_t ta = sb + OFF_PK + (uint32_t)(w * 16 + (lane & 15)) * 128;
#pragma unroll 1
      for (int g = 0; g < 13 - TL; g++) {
        const uint32_t r = g * 52 >> 8, s = g - r * 5;
        const uint32_t da = da0 + (g == OWN ? 5 : s) * (O_BYTES >> 4), db = db0 + s * (O_BYTES >> 4);
        if (g == OWN) {
          wg_wait<0>();
          mbar_arrive_warp(sb + BAR_EMPTY + (OWN + 4) % 5 * 8);
          mbar_wait(sb + BAR_OWN, 0);
        }
        mbar_wait(sb + BAR_FULL + s * 8, r & 1);
        if (chk >> g & 1) check_tile(g, s);
        PROF_C(wt == 0, 96 + g);
        wg_fence();
#pragma unroll
        for (int kk = 0; kk < 4; kk++)
#pragma unroll
          for (int m = 0; m < 2; m++) mma_out(acc[m], da + (m * 512 + kk * 2), db + kk * 128, kk ? 1 : g);
        wg_commit();
        wg_wait<1>();
        if (~(1 | 1 << OWN) >> g & 1) mbar_arrive_warp(sb + BAR_EMPTY + (s ? s - 1 : 4) * 8);
      }
      mbar_wait(sb + BAR_X, 0);
      if (((0xFFFF - (lds32(sb + OFF_MISC + 16) & 0xFFFF)) >> 7) == tm) mbar_wait(sb + BAR_Y, 0);
#pragma unroll
      for (int u = 0; u < 4; u++) {
        const int m = u >> 1, g = 13 - TL + u;
        const float g1 = 1.f - __uint_as_float(lds32(sb + OFF_G + (m * 64 + w * 16 + (u & 1) * 8 + (lane >> 2)) * 4));
        q[m][u & 1] = pack2(g1, g1);
#pragma unroll
        for (int j = 0; j < 4; j++) ldsm4(ta + (u & 1) * 16384 + m * 8192 + ((((lane >> 4) + 2 * j) ^ (lane & 7)) << 4), xr[m][(u & 1) * 4 + j]);
        if (u == 3) break;
        mbar_wait(sb + BAR_FULL + g % 5 * 8, g / 5 & 1);
        PROF_C(wt == 0, 96 + g);
        wg_fence();
#pragma unroll
        for (int kk = 0; kk < 4; kk++)
#pragma unroll
          for (int mm = 0; mm < 2; mm++)
            mma_out(acc[mm], da0 + (g % 5 * (O_BYTES >> 4) + mm * 512 + kk * 2), db0 + (g % 5 * (O_BYTES >> 4) + kk * 128), 1);
        wg_commit();
        wg_wait<1>();
        if (g <= 11) mbar_arrive_warp(sb + BAR_EMPTY + (g + 4) % 5 * 8);
      }
      auto half_step = [&](int m, int g) {
        if (m == 0) { mbar_wait(sb + BAR_FULL + g % 5 * 8, g / 5 & 1); PROF_C(wt == 0, 96 + g); wg_fence(); }
#pragma unroll
        for (int kk = 0; kk < 4; kk++)
          mma_out(acc[m], da0 + (g % 5 * (O_BYTES >> 4) + m * 512 + kk * 2), db0 + (g % 5 * (O_BYTES >> 4) + kk * 128), 1);
      };
      auto stage = [&](int m, int j0, int j1) {
#pragma unroll
        for (int j = j0; j < j1; j++) {
          const float* v = &acc[m][8 * j];
          stsm4(ta + (j >> 2) * 16384 + m * 8192 + ((((lane >> 4) + 2 * (j & 3)) ^ (lane & 7)) << 4),
                fma_bf2(xr[m][j][0], q[m][0], pack2(v[0], v[1])), fma_bf2(xr[m][j][1], q[m][1], pack2(v[2], v[3])),
                fma_bf2(xr[m][j][2], q[m][0], pack2(v[4], v[5])), fma_bf2(xr[m][j][3], q[m][1], pack2(v[6], v[7])));
        }
      };
      auto leave_tma = [&](int m, int h) {
        fence_async_smem();
        __syncwarp();
        if (elect()) tma2d_store(&p.out, sb + OFF_PK + h * 16384 + m * 8192 + w * 2048, tn * 128 + h * 64, tm * 128 + m * 64 + w * 16);
      };
      auto leave = [&](int m, int h) {
        __syncwarp();
        const uint32_t r = lane >> 3;
        uint4 v[4];
#pragma unroll
        for (int i = 0; i < 4; i++) v[i] = lds128(sb + OFF_PK + h * 16384 + m * 8192 + w * 2048 + (r + 4 * i) * 128 + (((lane ^ (r + 4 * i)) & 7) << 4));
        char* const dst = (char*)pout + (size_t)(tm * 128 + m * 64 + w * 16 + r) * (D_ * 2) + tn * 256 + h * 128 + (lane & 7) * 16;
#pragma unroll
        for (int i = 0; i < 4; i++) asm volatile("st.global.v4.u32 [%0], {%1, %2, %3, %4};" ::"l"(dst + i * 4 * D_ * 2), "r"(v[i].x), "r"(v[i].y), "r"(v[i].z), "r"(v[i].w) : "memory");
      };
#pragma unroll
      for (int g = 16 - TL; g < 16; g++) half_step(0, g);
      wg_commit();
#pragma unroll
      for (int g = 16 - TL; g < 16; g++) half_step(1, g);
      wg_commit();
      mbar_arrive_warp(sb + BAR_DONE);
      wg_wait<1>();
      PROF(wt == 0, 35);
      stage(0, 0, 4);
      leave_tma(0, 0);
      stage(0, 4, 8);
      leave_tma(0, 1);
      if (elect()) bulk_commit();
      PROF(wt == 0, 33);
      wg_wait<0>();
      PROF(wt == 0, 31);
#pragma unroll
      for (int h = 0; h < 2; h++) { stage(1, 4 * h, 4 * h + 4); leave(1, h); }
      if (elect()) asm volatile("cp.async.bulk.wait_group.read 0;" ::: "memory");
      PROF(wt == 0, 32);
    }
  }
}

typedef CUresult (*EncodeFn)(CUtensorMap*, CUtensorMapDataType, cuuint32_t, void*, const cuuint64_t*, const cuuint64_t*, const cuuint32_t*,
                             const cuuint32_t*, CUtensorMapInterleave, CUtensorMapSwizzle, CUtensorMapL2promotion, CUtensorMapFloatOOBfill);

void encode(EncodeFn fn, CUtensorMap* m, const void* ptr, int rank, const cuuint64_t* dims, const cuuint64_t* strides, const cuuint32_t* box,
            CUtensorMapSwizzle sw, CUtensorMapDataType dt = CU_TENSOR_MAP_DATA_TYPE_BFLOAT16) {
  const cuuint32_t es[3] = {1, 1, 1};
  fn(m, dt, rank, const_cast<void*>(ptr), dims, strides, box, es, CU_TENSOR_MAP_INTERLEAVE_NONE, sw,
     CU_TENSOR_MAP_L2_PROMOTION_L2_128B, CU_TENSOR_MAP_FLOAT_OOB_FILL_NONE);
}

}

extern "C" void kernel_launch(void* const* d_in, const int* in_sizes, int n_in, void* d_out, int out_size) {
  (void)in_sizes; (void)n_in; (void)out_size;
  EncodeFn fn = nullptr;
  cudaDriverEntryPointQueryResult qr;
  cudaGetDriverEntryPoint("cuTensorMapEncodeTiled", (void**)&fn, cudaEnableDefault, &qr);

  Params p;
  {
    const cuuint64_t dims[2] = {D_, S_}, str[1] = {D_ * 2};
    const cuuint32_t box[2] = {64, 128}, box_st[2] = {64, 16}, box_r[2] = {256, 16};
    encode(fn, &p.xr, d_in[0], 2, dims, str, box_r, CU_TENSOR_MAP_SWIZZLE_NONE);
    encode(fn, &p.x, d_in[0], 2, dims, str, box, CU_TENSOR_MAP_SWIZZLE_128B);
    encode(fn, &p.out, d_out, 2, dims, str, box_st, CU_TENSOR_MAP_SWIZZLE_128B);
  }
  {
    const cuuint64_t dims[3] = {D_, D_, 3}, str[2] = {3 * D_ * 2, D_ * 2};
    const cuuint32_t box[3] = {64, 64, 3};
    encode(fn, &p.w, d_in[1], 3, dims, str, box, CU_TENSOR_MAP_SWIZZLE_128B);
  }
  {
    const cuuint64_t dims[3] = {64, D_, D_ / 64}, str[2] = {D_ * 2, 128};
    const cuuint32_t box[3] = {64, 64, 2};
    encode(fn, &p.wo, d_in[2], 3, dims, str, box, CU_TENSOR_MAP_SWIZZLE_128B);
  }
  {
    const cuuint64_t dims[3] = {F_, D_ / 4, 4}, str[2] = {F_ * 8, F_ * 2};
    const cuuint32_t box[3] = {32, 16, 4};
    encode(fn, &p.gate, d_in[5], 3, dims, str, box, CU_TENSOR_MAP_SWIZZLE_NONE);
    encode(fn, &p.up, d_in[6], 3, dims, str, box, CU_TENSOR_MAP_SWIZZLE_NONE);
  }
  {
    const cuuint64_t dims[3] = {D_ / 4, F_, 2}, str[2] = {D_ * 2, D_};
    const cuuint32_t box[3] = {256, 4, 2};
    encode(fn, &p.down, d_in[7], 3, dims, str, box, CU_TENSOR_MAP_SWIZZLE_NONE, CU_TENSOR_MAP_DATA_TYPE_UINT32);
  }
  void* gs = nullptr;
  cudaGetSymbolAddress(&gs, g_scratch);
  typedef const __nv_bfloat16* bp;
  int dev = 0, sms = 0;
  cudaGetDevice(&dev);
  cudaDeviceGetAttribute(&sms, cudaDevAttrMultiProcessorCount, dev);
  const bool by_sm = BYSM && sms == NGRID;
  const auto kernel = by_sm ? fused_kernel<true> : fused_kernel<false>;
  cudaFuncSetAttribute(kernel, cudaFuncAttributeMaxDynamicSharedMemorySize, SMEM_BYTES);
  kernel<<<by_sm ? NGRID : NCTA, NTHREADS, SMEM_BYTES, cudaStreamPerThread>>>((bp)d_in[0], (Scratch*)gs, (bp)d_in[5], (bp)d_in[6], (bp)d_in[4], (bp)d_in[8], p, d_out);
}
```

```cpp
#include <cuda_runtime.h>
#include <cuda.h>
#include <cuda_bf16.h>
#include <stdint.h>
#include <stddef.h>

namespace {

constexpr int S_ = 2048, D_ = 1024, F_ = 3584;
constexpr int NCTA = 128, NGRID = 132, NTHREADS = 512;
constexpr int MOD_CTAS = F_ / 32;

#define PC 2
#define PRE 2
#define ST1 700
#define RT_G0 2
#define RT_ORD 0x1032
#define RT_SLEEP 500
#define PF_MOD 6
#define MOD_START 9
#define MM 4
#define PA 6
#define RED_SLEEP 32
#define RETRY 1
#define KV_SLEEP_A 128
#define KV_SLEEP 50
#define OWN 5
#define TL 3
#define NOMOD 5
#define FSL 256
#define M1 1
#define PAIRED 1
#define BYSM 1

constexpr uint32_t A_BYTES = 16384, BQ_BYTES = 24576, BO_BYTES = 16384, STAGE_BYTES = A_BYTES + BQ_BYTES, O_BYTES = A_BYTES + BO_BYTES;
constexpr int MOD_BUFS = 3, MOD_BUFS0 = MOD_BUFS + 1;
static_assert(MOD_START + MOD_BUFS0 <= 16, "first FFN round is requested during wave A");
constexpr uint32_t OFF_RING = 0;
constexpr uint32_t OFF_MOD = 4 * STAGE_BYTES;
constexpr uint32_t OFF_PK = OFF_MOD + MOD_BUFS * 8192;
constexpr uint32_t OFF_V = OFF_PK + 16384;
constexpr uint32_t OFF_ONES = OFF_V + 16384;
constexpr uint32_t OFF_KVB = OFF_ONES + 2048;
constexpr uint32_t OFF_XSEL = OFF_KVB + 5120;
constexpr uint32_t OFF_G = OFF_XSEL + 2048;
constexpr uint32_t OFF_PART = OFF_G + 512;
constexpr uint32_t OFF_MISC = OFF_PART + 576;
constexpr uint32_t OFF_BAR = OFF_MISC + 32;
constexpr uint32_t BAR_FULL = OFF_BAR, BAR_EMPTY = OFF_BAR + 40, BAR_RTD = OFF_BAR + 80, BAR_Y = OFF_BAR + 88, BAR_DONE = OFF_BAR + 96,
                   BAR_X = OFF_BAR + 104, BAR_OA = OFF_BAR + 112, BAR_OWN = OFF_BAR + 120, BAR_OST = OFF_BAR + 128, BAR_PA = OFF_BAR + 136,
                   BAR_W31 = OFF_BAR + 144, BAR_MFULL = OFF_BAR + 152, BAR_MEMPTY = BAR_MFULL + MOD_BUFS0 * 8,
                   BAR_IDX = BAR_MEMPTY + MOD_BUFS * 8;
constexpr uint32_t SMEM_BYTES = OFF_BAR + 384;
static_assert(SMEM_BYTES <= 232448, "smem");

constexpr uint32_t BAR_LAND = OFF_BAR + 256, BAR_FIX = BAR_LAND + 64;
constexpr uint32_t BAR_RT = BAR_FIX;
static_assert(TL == 3 && PRE == 2 && BAR_IDX - OFF_BAR < 256, "warp w initialises barriers 2w and 2w + 1");
constexpr __host__ __device__ uint64_t bar_counts(int first) {
  uint64_t r = 0;
  for (uint32_t i = 0; i < 16; i++) {
    const uint32_t b = OFF_BAR + (first + i) * 8;
    const uint64_t c = b < BAR_EMPTY ? 2 : b == BAR_IDX ? 5 : b == BAR_Y || b == BAR_X || (b >= BAR_PA && b < BAR_MEMPTY) ? 1 : 4;
    r |= c << i * 4;
  }
  return r;
}

constexpr int NB_WG0 = 1, NB_ORDER_AB = 3, NB_ORDER_BO = 4, NB_STG = 5, NB_MODW = 6, NB_KEY = 7, NB_CHK = 8;

constexpr int NV = 5, NCLR = NV * 4 + 5;
struct Scratch {
  float4 kv[2][8][NV][128];
  float y[8][D_];
  unsigned cnt[64][32];
  unsigned gslot[S_];
  unsigned rslot[8][NCTA];
  unsigned spare[128];
  unsigned block[NCTA];
  uint4 o[16][16][1024];
};
static_assert(offsetof(Scratch, gslot) == NCTA * NCLR * 64, "clear size");
__device__ __align__(1024) Scratch g_scratch;

#define PROF(cond, i) do {} while (0)
#define PROF_C(cond, i) do {} while (0)
#define PROF_P(cond, i) do {} while (0)
#define PROF_V(cond, i, v) do {} while (0)

__device__ __forceinline__ void mbar_init(uint32_t bar, int cnt) { asm volatile("mbarrier.init.shared::cta.b64 [%0], %1;" ::"r"(bar), "r"(cnt)); }
__device__ __forceinline__ void mbar_expect_tx(uint32_t bar, uint32_t bytes) { asm volatile("mbarrier.arrive.expect_tx.shared::cta.b64 _, [%0], %1;" ::"r"(bar), "r"(bytes) : "memory"); }
__device__ __forceinline__ void mbar_arrive(uint32_t bar) { asm volatile("mbarrier.arrive.shared::cta.b64 _, [%0];" ::"r"(bar) : "memory"); }
__device__ __forceinline__ uint32_t peer_addr(uint32_t a) {
  uint32_t r;
  asm volatile("{\n.reg .u32 c;\nmov.u32 c, %%cluster_ctarank;\nxor.b32 c, c, 1;\nmapa.shared::cluster.u32 %0, %1, c;\n}" : "=r"(r) : "r"(a));
  return r;
}
__device__ __forceinline__ void mbar_arrive_peer(uint32_t bar) { asm volatile("mbarrier.arrive.shared::cluster.b64 _, [%0];" ::"r"(bar) : "memory"); }
__device__ __forceinline__ uint32_t mism(uint32_t a, uint32_t b, uint32_t p) {
  uint32_t r; asm("lop3.b32 %0, %1, %2, %3, 0x7E;" : "=r"(r) : "r"(a), "r"(b), "r"(p)); return r;
}
__device__ __forceinline__ bool elect() {
  uint32_t r;
  asm volatile("{\n.reg .pred p;\nelect.sync _|p, 0xffffffff;\nselp.u32 %0, 1, 0, p;\n}" : "=r"(r));
  return r;
}
__device__ __forceinline__ uint32_t fresh_tid() { uint32_t r; asm volatile("mov.u32 %0, %%tid.x;" : "=r"(r)); return r; }
__device__ __forceinline__ void mbar_arrive_warp(uint32_t bar) {
  asm volatile("{\n.reg .pred p;\nelect.sync _|p, 0xffffffff;\n@p mbarrier.arrive.shared::cta.b64 _, [%0];\n}" ::"r"(bar) : "memory");
}
__device__ __forceinline__ void mbar_wait(uint32_t bar, uint32_t parity) {
  asm volatile("{\n.reg .pred p;\nWAIT_L:\nmbarrier.try_wait.parity.shared::cta.b64 p, [%0], %1;\n@p bra DONE_L;\nbra WAIT_L;\nDONE_L:\n}"
               ::"r"(bar), "r"(parity) : "memory");
}
__device__ __forceinline__ uint32_t mbar_test(uint32_t bar, uint32_t parity) {
  uint32_t ok;
  asm volatile("{\n.reg .pred p;\nmbarrier.test_wait.parity.shared::cta.b64 p, [%1], %2;\nselp.u32 %0, 1, 0, p;\n}" : "=r"(ok) : "r"(bar), "r"(parity) : "memory");
  return ok;
}
constexpr unsigned long long WATCHDOG_NS = 2000000000ull;
__device__ __forceinline__ unsigned long long gtime() { unsigned long long t; asm volatile("mov.u64 %0, %%globaltimer;" : "=l"(t)); return t; }
__device__ __forceinline__ uint32_t clock32() { uint32_t t; asm volatile("mov.u32 %0, %%clock;" : "=r"(t)); return t; }
__device__ __forceinline__ void mbar_wait_bounded(uint32_t bar, uint32_t parity) {
  unsigned long long t0 = 0;
  for (;;) {
    uint32_t ok;
    asm volatile("{\n.reg .pred p;\nmbarrier.try_wait.parity.shared::cta.b64 p, [%1], %2;\nselp.u32 %0, 1, 0, p;\n}" : "=r"(ok) : "r"(bar), "r"(parity) : "memory");
    if (ok) break;
    const unsigned long long t1 = gtime();
    if (t0 == 0) t0 = t1;
    if (t1 - t0 > WATCHDOG_NS) __trap();
  }
}
__device__ __forceinline__ void tma2d(uint32_t dst, const CUtensorMap* m, int c0, int c1, uint32_t bar) {
  asm volatile("cp.async.bulk.tensor.2d.shared::cluster.global.mbarrier::complete_tx::bytes [%0], [%1, {%3, %4}], [%2];"
               ::"r"(dst), "l"(m), "r"(bar), "r"(c0), "r"(c1) : "memory");
}
__device__ __forceinline__ void tma3d(uint32_t dst, const CUtensorMap* m, int c0, int c1, int c2, uint32_t bar) {
  asm volatile("cp.async.bulk.tensor.3d.shared::cluster.global.mbarrier::complete_tx::bytes [%0], [%1, {%3, %4, %5}], [%2];"
               ::"r"(dst), "l"(m), "r"(bar), "r"(c0), "r"(c1), "r"(c2) : "memory");
}
__device__ __forceinline__ void bulk_load(uint32_t dst, const void* src, uint32_t bytes, uint32_t bar) {
  asm volatile("cp.async.bulk.shared::cluster.global.mbarrier::complete_tx::bytes [%0], [%1], %2, [%3];" ::"r"(dst), "l"(src), "r"(bytes), "r"(bar) : "memory");
}
__device__ __forceinline__ void bulk_store(void* dst, uint32_t src, uint32_t bytes) {
  asm volatile("cp.async.bulk.global.shared::cta.bulk_group [%0], [%1], %2;" ::"l"(dst), "r"(src), "r"(bytes) : "memory");
}
__device__ __forceinline__ void bulk_push(uint32_t dst, uint32_t src, uint32_t bytes, uint32_t bar) {
  asm volatile("cp.async.bulk.shared::cluster.shared::cta.mbarrier::complete_tx::bytes [%0], [%1], %2, [%3];" ::"r"(dst), "r"(src), "r"(bytes), "r"(bar) : "memory");
}
__device__ __forceinline__ void bulk_commit() { asm volatile("cp.async.bulk.commit_group;" ::: "memory"); }
__device__ __forceinline__ void bulk_prefetch(const void* p, uint32_t bytes) {
  asm volatile("cp.async.bulk.prefetch.L2.global [%0], %1;" ::"l"(p), "r"(bytes) : "memory");
}
__device__ __forceinline__ void tma2d_store(const CUtensorMap* m, uint32_t src, int c0, int c1) {
  asm volatile("cp.async.bulk.tensor.2d.global.shared::cta.bulk_group [%0, {%2, %3}], [%1];" ::"l"(m), "r"(src), "r"(c0), "r"(c1) : "memory");
}
__device__ __forceinline__ void wg_fence() { asm volatile("wgmma.fence.sync.aligned;" ::: "memory"); }
__device__ __forceinline__ void wg_commit() { asm volatile("wgmma.commit_group.sync.aligned;" ::: "memory"); }
template <int N> __device__ __forceinline__ void wg_wait() { asm volatile("wgmma.wait_group.sync.aligned %0;" ::"n"(N) : "memory"); }
__device__ __forceinline__ void fence_async_smem() { asm volatile("fence.proxy.async.shared::cta;" ::: "memory"); }
__device__ __forceinline__ void fence_release() { asm volatile("fence.release.gpu;" ::: "memory"); }
__device__ __forceinline__ void fence_acquire() { asm volatile("fence.acquire.gpu;" ::: "memory"); }
__device__ __forceinline__ void nb_sync(int id, int n) { asm volatile("bar.sync %0, %1;" ::"r"(id), "r"(n) : "memory"); }
__device__ __forceinline__ void nb_arrive(int id, int n) { asm volatile("bar.arrive %0, %1;" ::"r"(id), "r"(n) : "memory"); }
__device__ __forceinline__ void stsm4(uint32_t addr, uint32_t r0, uint32_t r1, uint32_t r2, uint32_t r3) {
  asm volatile("stmatrix.sync.aligned.m8n8.x4.shared.b16 [%0], {%1, %2, %3, %4};" ::"r"(addr), "r"(r0), "r"(r1), "r"(r2), "r"(r3) : "memory");
}
__device__ __forceinline__ void sts128(uint32_t addr, uint32_t a, uint32_t b, uint32_t c, uint32_t d) {
  asm volatile("st.shared.v4.b32 [%0], {%1, %2, %3, %4};" ::"r"(addr), "r"(a), "r"(b), "r"(c), "r"(d) : "memory");
}
__device__ __forceinline__ uint32_t pack2(float lo, float hi) {
  uint32_t r; asm("cvt.rn.bf16x2.f32 %0, %1, %2;" : "=r"(r) : "f"(hi), "f"(lo)); return r;
}
__device__ __forceinline__ float bf_lo(uint32_t v) { return __uint_as_float(v << 16); }
__device__ __forceinline__ float bf_hi(uint32_t v) { return __uint_as_float(v & 0xffff0000u); }
__device__ __forceinline__ float bf_round(float v) { return __bfloat162float(__float2bfloat16_rn(v)); }
__device__ __forceinline__ void ldsm4(uint32_t addr, uint32_t (&r)[4]) {
  asm volatile("ldmatrix.sync.aligned.m8n8.x4.shared.b16 {%0, %1, %2, %3}, [%4];" : "=r"(r[0]), "=r"(r[1]), "=r"(r[2]), "=r"(r[3]) : "r"(addr) : "memory");
}
__device__ __forceinline__ uint4 lds128(uint32_t addr) {
  uint4 v; asm volatile("ld.volatile.shared.v4.u32 {%0, %1, %2, %3}, [%4];" : "=r"(v.x), "=r"(v.y), "=r"(v.z), "=r"(v.w) : "r"(addr) : "memory"); return v;
}
__device__ __forceinline__ uint2 lds64(uint32_t addr) { uint2 v; asm volatile("ld.volatile.shared.v2.u32 {%0, %1}, [%2];" : "=r"(v.x), "=r"(v.y) : "r"(addr) : "memory"); return v; }
__device__ __forceinline__ uint32_t lds32(uint32_t addr) { uint32_t v; asm volatile("ld.volatile.shared.u32 %0, [%1];" : "=r"(v) : "r"(addr) : "memory"); return v; }
__device__ __forceinline__ void sts32(uint32_t addr, uint32_t v) { asm volatile("st.shared.u32 [%0], %1;" ::"r"(addr), "r"(v) : "memory"); }
__device__ __forceinline__ uint32_t fma_bf2(uint32_t a, uint32_t b, uint32_t c) { uint32_t r; asm("fma.rn.bf16x2 %0, %1, %2, %3;" : "=r"(r) : "r"(a), "r"(b), "r"(c)); return r; }
__device__ __forceinline__ unsigned ld_relaxed(const unsigned* p) { unsigned v; asm volatile("ld.relaxed.gpu.global.u32 %0, [%1];" : "=r"(v) : "l"(p) : "memory"); return v; }
__device__ __forceinline__ void st_relaxed(unsigned* p, unsigned v) { asm volatile("st.relaxed.gpu.global.u32 [%0], %1;" ::"l"(p), "r"(v) : "memory"); }
__device__ __forceinline__ uint4 ld_relaxed4(const void* p) {
  uint4 v; asm volatile("ld.relaxed.gpu.global.v4.u32 {%0, %1, %2, %3}, [%4];" : "=r"(v.x), "=r"(v.y), "=r"(v.z), "=r"(v.w) : "l"(p) : "memory"); return v;
}
__device__ __forceinline__ float4 ld_relaxed_f4(const void* p) {
  float4 v; asm volatile("ld.relaxed.gpu.global.v4.f32 {%0, %1, %2, %3}, [%4];" : "=f"(v.x), "=f"(v.y), "=f"(v.z), "=f"(v.w) : "l"(p) : "memory"); return v;
}
__device__ __forceinline__ void red_add4(void* p, float a, float b, float c, float d) {
  asm volatile("red.relaxed.gpu.global.add.v4.f32 [%0], {%1, %2, %3, %4};" ::"l"(p), "f"(a), "f"(b), "f"(c), "f"(d) : "memory");
}
__device__ __forceinline__ void red_add(unsigned* p, unsigned v) { asm volatile("red.relaxed.gpu.global.add.u32 [%0], %1;" ::"l"(p), "r"(v) : "memory"); }
__device__ __forceinline__ void wait_counter(const unsigned* p, unsigned target) {
  while (ld_relaxed(p) < target) __nanosleep(32);
  fence_acquire();
}
__device__ __forceinline__ float rcp(float v) { float r; asm("rcp.approx.ftz.f32 %0, %1;" : "=f"(r) : "f"(v)); return r; }
__device__ __forceinline__ float sigmoidf_(float v) { return rcp(1.f + __expf(-v)); }
__device__ __forceinline__ uint32_t phi2(float a, float b, float l2e = 1.4426950408889634f) {
  float ea, eb;
  asm("ex2.approx.ftz.f32 %0, %1;" : "=f"(ea) : "f"(a * l2e));
  asm("ex2.approx.ftz.f32 %0, %1;" : "=f"(eb) : "f"(b * l2e));
  uint32_t t = pack2(a, b), e = pack2(ea, eb), r;
  asm("max.NaN.bf16x2 %0, %0, %1;" : "+r"(t) : "r"(0x35863586u));
  asm("min.bf16x2 %0, %0, %1;" : "+r"(e) : "r"(0x3F803F80u));
  asm("add.rn.bf16x2 %0, %1, %2;" : "=r"(r) : "r"(t), "r"(e));
  return r;
}
__device__ __forceinline__ uint32_t mkdesc(uint32_t addr, uint32_t lbo) { return ((addr & 0x3FFFF) >> 4) | ((lbo >> 4) << 16); }

__device__ __forceinline__ void mma_qkv(float (&d)[96], uint32_t da, uint32_t db, int sc) {
  asm volatile("{\n.reg .pred p;\n.reg .b64 da, db;\nmov.b64 da, {%96, 0x40000040};\nmov.b64 db, {%97, 0x40000040};\nsetp.ne.b32 p, %98, 0;\n"
    "wgmma.mma_async.sync.aligned.m64n192k16.f32.bf16.bf16 "
    "{%0,%1,%2,%3,%4,%5,%6,%7,%8,%9,%10,%11,%12,%13,%14,%15,%16,%17,%18,%19,%20,%21,%22,%23,"
    "%24,%25,%26,%27,%28,%29,%30,%31,%32,%33,%34,%35,%36,%37,%38,%39,%40,%41,%42,%43,%44,%45,%46,%47,"
    "%48,%49,%50,%51,%52,%53,%54,%55,%56,%57,%58,%59,%60,%61,%62,%63,%64,%65,%66,%67,%68,%69,%70,%71,"
    "%72,%73,%74,%75,%76,%77,%78,%79,%80,%81,%82,%83,%84,%85,%86,%87,%88,%89,%90,%91,%92,%93,%94,%95}, "
    "da, db, p, 1, 1, 0, 1;\n}\n"
    : "+f"(d[0]), "+f"(d[1]), "+f"(d[2]), "+f"(d[3]), "+f"(d[4]), "+f"(d[5]), "+f"(d[6]), "+f"(d[7]),
      "+f"(d[8]), "+f"(d[9]), "+f"(d[10]), "+f"(d[11]), "+f"(d[12]), "+f"(d[13]), "+f"(d[14]), "+f"(d[15]),
      "+f"(d[16]), "+f"(d[17]), "+f"(d[18]), "+f"(d[19]), "+f"(d[20]), "+f"(d[21]), "+f"(d[22]), "+f"(d[23]),
      "+f"(d[24]), "+f"(d[25]), "+f"(d[26]), "+f"(d[27]), "+f"(d[28]), "+f"(d[29]), "+f"(d[30]), "+f"(d[31]),
      "+f"(d[32]), "+f"(d[33]), "+f"(d[34]), "+f"(d[35]), "+f"(d[36]), "+f"(d[37]), "+f"(d[38]), "+f"(d[39]),
      "+f"(d[40]), "+f"(d[41]), "+f"(d[42]), "+f"(d[43]), "+f"(d[44]), "+f"(d[45]), "+f"(d[46]), "+f"(d[47]),
      "+f"(d[48]), "+f"(d[49]), "+f"(d[50]), "+f"(d[51]), "+f"(d[52]), "+f"(d[53]), "+f"(d[54]), "+f"(d[55]),
      "+f"(d[56]), "+f"(d[57]), "+f"(d[58]), "+f"(d[59]), "+f"(d[60]), "+f"(d[61]), "+f"(d[62]), "+f"(d[63]),
      "+f"(d[64]), "+f"(d[65]), "+f"(d[66]), "+f"(d[67]), "+f"(d[68]), "+f"(d[69]), "+f"(d[70]), "+f"(d[71]),
      "+f"(d[72]), "+f"(d[73]), "+f"(d[74]), "+f"(d[75]), "+f"(d[76]), "+f"(d[77]), "+f"(d[78]), "+f"(d[79]),
      "+f"(d[80]), "+f"(d[81]), "+f"(d[82]), "+f"(d[83]), "+f"(d[84]), "+f"(d[85]), "+f"(d[86]), "+f"(d[87]),
      "+f"(d[88]), "+f"(d[89]), "+f"(d[90]), "+f"(d[91]), "+f"(d[92]), "+f"(d[93]), "+f"(d[94]), "+f"(d[95])
    : "r"(da), "r"(db), "r"(sc));
}

__device__ __forceinline__ void mma_out(float (&d)[64], uint32_t da, uint32_t db, int sc) {
  asm volatile("{\n.reg .pred p;\n.reg .b64 da, db;\nmov.b64 da, {%64, 0x40000040};\nmov.b64 db, {%65, 0x40000040};\nsetp.ne.b32 p, %66, 0;\n"
    "wgmma.mma_async.sync.aligned.m64n128k16.f32.bf16.bf16 "
    "{%0,%1,%2,%3,%4,%5,%6,%7,%8,%9,%10,%11,%12,%13,%14,%15,%16,%17,%18,%19,%20,%21,%22,%23,"
    "%24,%25,%26,%27,%28,%29,%30,%31,%32,%33,%34,%35,%36,%37,%38,%39,%40,%41,%42,%43,%44,%45,%46,%47,"
    "%48,%49,%50,%51,%52,%53,%54,%55,%56,%57,%58,%59,%60,%61,%62,%63}, "
    "da, db, p, 1, 1, 0, 1;\n}\n"
    : "+f"(d[0]), "+f"(d[1]), "+f"(d[2]), "+f"(d[3]), "+f"(d[4]), "+f"(d[5]), "+f"(d[6]), "+f"(d[7]),
      "+f"(d[8]), "+f"(d[9]), "+f"(d[10]), "+f"(d[11]), "+f"(d[12]), "+f"(d[13]), "+f"(d[14]), "+f"(d[15]),
      "+f"(d[16]), "+f"(d[17]), "+f"(d[18]), "+f"(d[19]), "+f"(d[20]), "+f"(d[21]), "+f"(d[22]), "+f"(d[23]),
      "+f"(d[24]), "+f"(d[25]), "+f"(d[26]), "+f"(d[27]), "+f"(d[28]), "+f"(d[29]), "+f"(d[30]), "+f"(d[31]),
      "+f"(d[32]), "+f"(d[33]), "+f"(d[34]), "+f"(d[35]), "+f"(d[36]), "+f"(d[37]), "+f"(d[38]), "+f"(d[39]),
      "+f"(d[40]), "+f"(d[41]), "+f"(d[42]), "+f"(d[43]), "+f"(d[44]), "+f"(d[45]), "+f"(d[46]), "+f"(d[47]),
      "+f"(d[48]), "+f"(d[49]), "+f"(d[50]), "+f"(d[51]), "+f"(d[52]), "+f"(d[53]), "+f"(d[54]), "+f"(d[55]),
      "+f"(d[56]), "+f"(d[57]), "+f"(d[58]), "+f"(d[59]), "+f"(d[60]), "+f"(d[61]), "+f"(d[62]), "+f"(d[63])
    : "r"(da), "r"(db), "r"(sc));
}

__device__ __forceinline__ void mma_ktv(float (&d)[36], uint32_t da, uint32_t db, int sc) {
  asm volatile("{\n.reg .pred p;\n.reg .b64 da, db;\nmov.b64 da, {%36, 0x40000040};\nmov.b64 db, {%37, 0x40000040};\nsetp.ne.b32 p, %38, 0;\n"
    "wgmma.mma_async.sync.aligned.m64n72k16.f32.bf16.bf16 "
    "{%0,%1,%2,%3,%4,%5,%6,%7,%8,%9,%10,%11,%12,%13,%14,%15,%16,%17,%18,%19,%20,%21,%22,%23,"
    "%24,%25,%26,%27,%28,%29,%30,%31,%32,%33,%34,%35}, "
    "da, db, p, 1, 1, 1, 1;\n}\n"
    : "+f"(d[0]), "+f"(d[1]), "+f"(d[2]), "+f"(d[3]), "+f"(d[4]), "+f"(d[5]), "+f"(d[6]), "+f"(d[7]),
      "+f"(d[8]), "+f"(d[9]), "+f"(d[10]), "+f"(d[11]), "+f"(d[12]), "+f"(d[13]), "+f"(d[14]), "+f"(d[15]),
      "+f"(d[16]), "+f"(d[17]), "+f"(d[18]), "+f"(d[19]), "+f"(d[20]), "+f"(d[21]), "+f"(d[22]), "+f"(d[23]),
      "+f"(d[24]), "+f"(d[25]), "+f"(d[26]), "+f"(d[27]), "+f"(d[28]), "+f"(d[29]), "+f"(d[30]), "+f"(d[31]),
      "+f"(d[32]), "+f"(d[33]), "+f"(d[34]), "+f"(d[35])
    : "r"(da), "r"(db), "r"(sc));
}

__device__ __forceinline__ void mma_qkvz(float (&d)[20], const uint32_t (&a)[4], uint32_t db, int sc) {
  asm volatile("{\n.reg .pred p;\n.reg .b64 db;\nmov.b64 db, {%24, 0x20};\nsetp.ne.b32 p, %25, 0;\n"
    "wgmma.mma_async.sync.aligned.m64n40k16.f32.bf16.bf16 "
    "{%0,%1,%2,%3,%4,%5,%6,%7,%8,%9,%10,%11,%12,%13,%14,%15,%16,%17,%18,%19}, "
    "{%20,%21,%22,%23}, db, p, 1, 1, 1;\n}\n"
    : "+f"(d[0]), "+f"(d[1]), "+f"(d[2]), "+f"(d[3]), "+f"(d[4]), "+f"(d[5]), "+f"(d[6]), "+f"(d[7]),
      "+f"(d[8]), "+f"(d[9]), "+f"(d[10]), "+f"(d[11]), "+f"(d[12]), "+f"(d[13]), "+f"(d[14]), "+f"(d[15]),
      "+f"(d[16]), "+f"(d[17]), "+f"(d[18]), "+f"(d[19])
    : "r"(a[0]), "r"(a[1]), "r"(a[2]), "r"(a[3]), "r"(db), "r"(sc));
}

struct Params {
  CUtensorMap x, w, xr, wo, out, gate, up, down;
};

__device__ __forceinline__ void fma8(float (&acc)[8], const uint4& w, float m) {
  acc[0] = fmaf(bf_lo(w.x), m, acc[0]); acc[1] = fmaf(bf_hi(w.x), m, acc[1]);
  acc[2] = fmaf(bf_lo(w.y), m, acc[2]); acc[3] = fmaf(bf_hi(w.y), m, acc[3]);
  acc[4] = fmaf(bf_lo(w.z), m, acc[4]); acc[5] = fmaf(bf_hi(w.z), m, acc[5]);
  acc[6] = fmaf(bf_lo(w.w), m, acc[6]); acc[7] = fmaf(bf_hi(w.w), m, acc[7]);
}
__device__ __forceinline__ float butterfly8(float (&s)[8], int lane, int o) {
#pragma unroll
  for (int k = 1; k < 8; k <<= 1) {
    const bool up = lane & (o * k);
#pragma unroll
    for (int j = 0; j < 4 / k; j++) s[j] = (up ? s[2 * j + 1] : s[2 * j]) + __shfl_xor_sync(~0u, up ? s[2 * j] : s[2 * j + 1], o * k);
  }
  return s[0];
}
constexpr int PEER = 9;
constexpr __host__ __device__ uint32_t step_list() {
  uint32_t r = 0;
  for (int j = PEER - 1; j >= 0; j--) if (j != OWN) r = r << 4 | j % 5 | (j < 5) << 3;
  return r;
}
template <bool BY_SM> struct Tile {
  int sm, tm, tn, mu;
  bool spare;
  __device__ __forceinline__ Tile() {
    if (BY_SM) asm volatile("mov.u32 %0, %%smid;" : "=r"(sm));
    else sm = blockIdx.x + (blockIdx.x >= 120) * 4;
    const int tp = sm >> 1, pr = sm & 1;
    const int v = tp < 32 ? tp : tp < 60 ? (tp * 293 - 928) >> 8 : tp * 8 - 464, g = v & 7, i = v >> 3;
    const int j = i * 11 >> 5, c = i - j * 3;
    tm = (v & 6) * 2 + (c < 2 ? j : 3); tn = (v & 1) * 4 + (c < 2 ? c : j) * 2 + pr;
    mu = i == NOMOD ? 112 : g * 14 + (i - (i > NOMOD)) * 2 + pr;
    spare = (tp | 1) == 61;
  }
};

template <bool BY_SM> __global__ void __cluster_dims__(2, 1, 1) __launch_bounds__(NTHREADS, 1) fused_kernel(const __nv_bfloat16* __restrict__ px, Scratch* gs, const __nv_bfloat16* __restrict__ w_gate,
             const __nv_bfloat16* __restrict__ w_up, const __nv_bfloat16* __restrict__ w_r, const __nv_bfloat16* __restrict__ gate_w,
             const __grid_constant__ Params p, void* pout) {
  extern __shared__ __align__(1024) uint8_t smem[];
  const uint32_t sb = __shfl_sync(~0u, (uint32_t)__cvta_generic_to_shared(smem), 0);
  const int tid = threadIdx.x, lane = tid & 31;
  const int warp = __shfl_sync(~0u, tid >> 5, 0), wg = warp >> 2;
  const uint32_t t_start = clock32();
  const Tile<BY_SM> tile;
  const int tm = tile.tm, tn = tile.tn, mu = tile.mu, cta = tm * 8 + tn;
  {
    const uint32_t cnt = (uint32_t)((warp & 8 ? bar_counts(16) : bar_counts(0)) >> (warp & 7) * 8);
    if (elect()) mbar_init(sb + OFF_BAR + warp * 16, cnt & 15);
    if (elect()) mbar_init(sb + OFF_BAR + warp * 16 + 8, cnt >> 4 & 15);
    if (elect()) mbar_init(sb + BAR_LAND + warp * 8, 1);
    asm volatile("fence.mbarrier_init.release.cluster;" ::: "memory");
  }
  if (warp == 0 && !tile.spare) {
#pragma unroll
    for (int s = 0; s < PRE; s++) {
      if (elect()) tma3d(sb + OFF_RING + s * STAGE_BYTES + A_BYTES, &p.w, tn * 64, s * 64, 0, sb + BAR_FULL + s * 8);
      if (elect()) tma2d(sb + OFF_RING + s * STAGE_BYTES, &p.x, s * 64, tm * 128, sb + BAR_FULL + s * 8);
      PROF_P(lane == 0, 64 + s);
    }
    if (elect()) {
#pragma unroll
      for (int s = 0; s < PRE; s++) { mbar_expect_tx(sb + BAR_FULL + s * 8, STAGE_BYTES); mbar_arrive(sb + BAR_FULL + s * 8); }
    }
  }
  asm volatile("" ::: "memory");
  if (warp == 5) {
#pragma unroll
    for (int i = 0; i < 4; i++) sts128(sb + OFF_ONES + i * 512 + lane * 16, 0x3F803F80u, 0x3F803F80u, 0x3F803F80u, 0x3F803F80u);
    sts32(sb + OFF_MISC + 20, 0x3FB8AA3Bu);
    fence_async_smem();
  }
  __syncthreads();
  if (tile.spare) {
    if (warp == 0) {
      const unsigned tag = (ld_relaxed(&gs->spare[tile.sm & 3]) + 1) & 0xFFF;
      const unsigned long long t0 = gtime();
      uint4 r4;
      do {
        __nanosleep(2048);
        if (gtime() - t0 > WATCHDOG_NS) __trap();
        r4 = ld_relaxed4(&gs->rslot[tile.sm & 3][lane * 4]);
      } while (!__all_sync(~0u, (((r4.x ^ tag) | (r4.y ^ tag) | (r4.z ^ tag) | (r4.w ^ tag)) & 0xFFF) == 0));
      if (tid == 0) st_relaxed(&gs->spare[tile.sm & 3], tag);
    }
    return;
  }

  if (wg == 3) {
    asm volatile("setmaxnreg.dec.sync.aligned.u32 24;");
    if (warp == 12) {
      mbar_wait(sb + BAR_W31, 0);
      mbar_wait(sb + BAR_IDX, 0);
      const uint32_t lowb = (1u << (tn & 6) * 4) - 1;
      uint32_t slabs = 0x76543210u, steps = step_list();
      const uint4* src = gs->o[tm][0];
      unsigned seen = 0;
#pragma unroll 1
      for (int n = 8; n >= 6; n -= 2) {
#pragma unroll 1
        for (int i = 0; i < n; i++, slabs >>= 4, steps >>= 4) {
          const uint32_t s = steps & 7, full = sb + BAR_FULL + s * 8, need = 4u << (slabs & 7) * 4;
          const uint32_t land = n == 8 ? full : sb + BAR_LAND + i * 8;
          mbar_wait(full + (BAR_EMPTY - BAR_FULL), steps >> 3 & 1);
          PROF(lane == 0 && (!PROFC || n == 6), 224 + i + (n == 6) * 10);
          if (!__all_sync(~0u, seen & need)) {
            while (!__all_sync(~0u, (seen = ld_relaxed(gs->cnt[tm])) & need)) __nanosleep(FSL);
          }
          if (elect()) bulk_load(sb + OFF_RING + s * O_BYTES, src + (slabs & 7) * 1024, A_BYTES, land);
          if (elect()) mbar_expect_tx(land, A_BYTES);
          PROF(lane == 0 && (!PROFC || n == 6), 240 + i + (n == 6) * 10);
        }
        slabs = (0x76543210u & lowb) | (0x765432u & ~lowb);
        steps = 0x0CBA98u;
        src += 8 * 1024;
      }
    } else if (warp == 13) {
      uint32_t full = sb + BAR_FULL + PRE * 8, dst = sb + OFF_RING + PRE * STAGE_BYTES + A_BYTES, c0 = tn * 64, c1 = PRE * 64;
#pragma unroll 1
      for (int g = PRE; g < 32; g++) {
        if (g < 4) while ((int)(clock32() - t_start) < g * ST1) {}
        const bool reuse = (g >> 2) == 4;
        mbar_wait(full + (BAR_EMPTY - BAR_FULL), ((g >> 2) & 1) ^ 1);
        if (!reuse && elect()) tma2d(dst - A_BYTES, &p.x, c1, tm * 128, full);
        if (elect()) tma3d(dst, &p.w, c0, c1, 0, full);
        if (elect()) { mbar_expect_tx(full, reuse ? BQ_BYTES : STAGE_BYTES); mbar_arrive(full); }

        PROF_P(lane == 0, 64 + g);
        const uint32_t i = g - RT_G0;
        if (i < 4 && elect()) {
          mbar_expect_tx(sb + BAR_RT + i * 8, i ? 8192 : 8192 + 4096);
          tma2d(sb + OFF_PK + i * 8192, &p.xr, (RT_ORD >> i * 4 & 3) * 256, cta * 16, sb + BAR_RT + i * 8);
          if (i == 0) { bulk_load(sb + OFF_KVB, w_r, 2048, sb + BAR_RT); bulk_load(sb + OFF_KVB + 2048, gate_w, 2048, sb + BAR_RT); }
        }
        const uint32_t c = g - MOD_START;
        if (c == MOD_BUFS) mbar_wait(sb + BAR_RTD, 0);
        if (c < MOD_BUFS0 && mu < MOD_CTAS && elect()) {
          PROF_P(true, 192 + c);
          const uint32_t mfull = sb + BAR_MFULL + c * 8, mdst = sb + OFF_MOD + c * 8192;
          mbar_expect_tx(mfull, c ? 8192 : 8192 + 2048);
          tma3d(mdst, &p.gate, mu * 32, c * 16, 0, mfull); tma3d(mdst + 4096, &p.up, mu * 32, c * 16, 0, mfull);
        }
        const uint32_t pc = g - PF_MOD;
        if (pc < 16 && elect()) bulk_prefetch((cta & 64 ? w_up : w_gate) + (size_t)(pc * 64 + (cta & 63)) * F_, F_ * 2);
        full += 8; dst += STAGE_BYTES; c1 += 64;
        if ((g & 3) == 3) { full -= 32; dst -= 4 * STAGE_BYTES; }
        if (g == 15) { c0 += 512; c1 = 768; }
        if (g == 19) c1 = 0;
      }
      mbar_arrive_warp(sb + BAR_W31);
      const uint32_t lowb = (1u << (tn & 6) * 4) - 1;
      uint64_t slabs = (uint64_t)((0xFEDCBA98u & lowb) | (0xFEDCBAu & ~lowb)) << 40 | (uint64_t)(8 + (tn ^ 1)) << 36 | (uint64_t)(8 + tn) << OWN * 4 |
                       (0x76543210ull & ~(~0ull << OWN * 4)) | (0x765432100ull & ~0ull << (OWN * 4 + 4));
      uint32_t ph = 1;
      c1 = 0;
#pragma unroll 1
      for (int g = 0; g < 16; g++) {
        mbar_wait(full + (BAR_EMPTY - BAR_FULL), ph);
        if (elect()) tma3d(dst, &p.wo, 0, c1, tn * 2, full);
        if (elect()) mbar_expect_tx(full, BO_BYTES);
        PROF_P(lane == 0, 96 + g);
        if (g == OWN && elect()) mbar_arrive(full);
        full += 8; dst += O_BYTES; slabs >>= 4; c1 = ((uint32_t)slabs & 15) * 64;
        if (full == sb + BAR_EMPTY) { full -= 40; dst -= 5 * O_BYTES; ph ^= 1; }
      }
    } else if (warp == 14) {
      if (mu < MOD_CTAS) {
        uint32_t full = sb + BAR_MFULL, dst = sb + OFF_MOD, ph = 0;
#pragma unroll 1
        for (int c = MOD_BUFS0; c < 24; c++) {
          mbar_wait(full + (BAR_MEMPTY - BAR_MFULL), ph);
          PROF_P(lane == 0, 192 + c);
          if (c < 16) {
            if (elect()) { tma3d(dst, &p.gate, mu * 32, c * 16, 0, full); tma3d(dst + 4096, &p.up, mu * 32, c * 16, 0, full); }
          } else if (elect()) tma3d(dst, &p.down, 0, mu * 32 + (c - 16) * 4, 0, full);
          if (elect()) mbar_expect_tx(full, 8192);
          full += 8; dst += 8192;
          if (dst == sb + OFF_PK) { full -= MOD_BUFS * 8; dst = sb + OFF_MOD; ph ^= 1; }
        }
      }
      if (elect()) {
      mbar_wait(sb + BAR_IDX, 0);
      const bool paired = lds32(sb + OFF_MISC + 28) < 0x200;
      const uint32_t pb = peer_addr(sb);
      mbar_wait(sb + BAR_EMPTY + PEER % 5 * 8, 0);
      mbar_expect_tx(sb + BAR_FULL + PEER % 5 * 8, A_BYTES);
      if (paired) mbar_arrive_peer(pb + BAR_PA);
      mbar_wait(sb + BAR_OST, 0);
      mbar_expect_tx(sb + BAR_X, 32768);
      tma2d(sb + OFF_PK, &p.x, tn * 128, tm * 128, sb + BAR_X);
      tma2d(sb + OFF_V, &p.x, tn * 128 + 64, tm * 128, sb + BAR_X);
      if (paired) {
        mbar_wait(sb + BAR_PA, 0);
        mbar_wait(sb + BAR_OWN, 0);
        bulk_push(pb + OFF_RING + PEER % 5 * O_BYTES, sb + OFF_MOD, A_BYTES, pb + BAR_FULL + PEER % 5 * 8);
        mbar_wait(sb + BAR_EMPTY + PEER % 5 * 8, 1);
        mbar_arrive_peer(pb + BAR_PA);
        mbar_wait(sb + BAR_PA, 1);
      } else {
        mbar_wait(sb + BAR_OWN, 0);
        __nanosleep(500);
        bulk_load(sb + OFF_RING + PEER % 5 * O_BYTES, gs->o[tm][8 + (tn ^ 1)], A_BYTES, sb + BAR_FULL + PEER % 5 * 8);
      }
      }
    } else if (elect()) {
#pragma unroll 1
      for (int i = 2; i < 8; i++) asm volatile("prefetch.tensormap [%0];" ::"l"(&p.x + i) : "memory");
      mbar_wait_bounded(sb + BAR_DONE, 0);
    }
  } else if (wg == 2) {
    asm volatile("setmaxnreg.dec.sync.aligned.u32 40;");
    const int mw = warp & 3;
    if (mw == 0) {
      const unsigned tag = (ld_relaxed(&gs->rslot[tn][cta]) + 1) & 0xFFF;
#pragma unroll
      for (int i = 0; i < 4; i++)
        if (lane < NCLR) ((float4*)gs)[cta * (NCLR * 4) + i * NCLR + lane] = make_float4(0.f, 0.f, 0.f, 0.f);
      if (lane == 29) st_relaxed(&gs->block[cta], blockIdx.x << 12 | tag);
      fence_release();
      nb_sync(NB_KEY, 160);
      const uint4 k4 = lds128(sb + OFF_MISC);
      if (lane < 8) st_relaxed(&gs->rslot[lane][cta], max(max(k4.x, k4.y), max(k4.z, k4.w)) | tag);
      if (lane < 16) st_relaxed(&gs->gslot[cta * 16 + lane], lds32(sb + OFF_G + lane * 4) | tag);
      PROF(lane == 0, 20);
      uint4 r4;
      do {
        __nanosleep(RT_SLEEP);
        r4 = ld_relaxed4(&gs->rslot[tn][lane * 4]);
      } while (!__all_sync(~0u, (((r4.x ^ tag) | (r4.y ^ tag) | (r4.z ^ tag) | (r4.w ^ tag)) & 0xFFF) == 0));
      const int c0 = 0xFFF0 - lane * 64;
      unsigned key = max(max((r4.x & 0xFFFF0000u) | (c0 + ((r4.x >> 12) & 15)), (r4.y & 0xFFFF0000u) | (c0 - 16 + ((r4.y >> 12) & 15))),
                         max((r4.z & 0xFFFF0000u) | (c0 - 32 + ((r4.z >> 12) & 15)), (r4.w & 0xFFFF0000u) | (c0 - 48 + ((r4.w >> 12) & 15))));
      key = __reduce_max_sync(~0u, key);
      if (elect()) {
        sts32(sb + OFF_MISC + 16, key);
        sts32(sb + OFF_MISC + 24, tag & 1);
        if (mu < MOD_CTAS) bulk_load(sb + OFF_XSEL, px + (size_t)(0xFFFF - (key & 0xFFFF)) * D_, 2048, sb + BAR_MFULL);
      }
      PROF(lane == 0, 21);
      unsigned nb;
      do {
        r4 = ld_relaxed4(&gs->gslot[tm * 128 + lane * 4]);
        nb = ld_relaxed(&gs->block[cta ^ 1]);
      } while (!__all_sync(~0u, (((r4.x ^ tag) | (r4.y ^ tag) | (r4.z ^ tag) | (r4.w ^ tag) | (nb ^ tag)) & 0xFFF) == 0));
      sts128(sb + OFF_G + lane * 16, r4.x & 0xFFFF0000u, r4.y & 0xFFFF0000u, r4.z & 0xFFFF0000u, r4.w & 0xFFFF0000u);
      sts32(sb + OFF_MISC + 28, (PAIRED && nb >> 12 == (blockIdx.x ^ 1) ? 0x1FF : 0x3FF) & ~((1 << PC) - 1 | 1 << OWN));
      fence_acquire();
      __syncwarp();
      mbar_arrive_warp(sb + BAR_IDX);
    }
    PROF(tid == 256, 22);
    if (mu >= MOD_CTAS) {
      mbar_arrive_warp(sb + BAR_IDX);
      mbar_arrive_warp(sb + BAR_OA);
    } else {
      const uint32_t wp = sb + OFF_MOD + (mw >> 1) * 4096 + (mw & 1) * 512 + lane * 16;
      uint32_t mp = sb + OFF_XSEL - 128 + (mw & 1) * 64 + (lane >> 2) * 8, mc = 128;
      float acc[8] = {0.f, 0.f, 0.f, 0.f, 0.f, 0.f, 0.f, 0.f};
      uint32_t b = ~0u, ph = 0, a = sb + OFF_ONES - 3072;
      float m3 = 0.f;
      const uint32_t zero = lds32(sb + OFF_ONES) & 1;
      uint2 m = make_uint2(0, 0);
      uint4 w0 = make_uint4(0, 0, 0, 0), w1 = w0, w2 = w0, w3 = w0;
#pragma unroll 1
      for (int c = -1;; c++) {
        fma8(acc, w3, m3);
        w3 = lds128(a + 3072);
        const uint32_t rel = sb + BAR_MEMPTY + b * 8;
        if (c == 16) {
          const uint32_t ft = fresh_tid(), fl = ft & 31;
          sts32(sb + OFF_PART + (ft & 96) * 4 + ((ft & 3) * 8 + (fl >> 2)) * 4, __float_as_uint(butterfly8(acc, fl, 4)));
          nb_sync(NB_MODW, 128);
          const float* part = (const float*)(smem + OFF_PART) + fl;
          const float gp = bf_round(part[0] + part[32]), up = bf_round(part[64] + part[96]);
          *(__nv_bfloat16*)(smem + OFF_PART + 512 + fl * 2) = __float2bfloat16_rn(bf_round(gp * sigmoidf_(gp)) * up);
          __syncwarp();
          mp = sb + OFF_PART + 512; mc = 8;
          m = lds64(mp);
#pragma unroll
          for (int i = 0; i < 8; i++) acc[i] = 0.f;
          PROF(lane == 0 && mw == 0, 23);
        }
        if (++b == (c < MOD_BUFS0 ? MOD_BUFS0 : MOD_BUFS)) { b = 0; ph ^= 1; }
        const uint32_t ok = mbar_test(sb + BAR_MFULL + b * 8, ph);
        fma8(acc, w0, bf_lo(m.x));
        if (c >= 0) mbar_arrive_warp(rel + ((w3.x | __float_as_uint(acc[7])) & zero));
        fma8(acc, w1, bf_hi(m.x));
        fma8(acc, w2, bf_lo(m.y));
        m3 = bf_hi(m.y);
        if (c == 23) break;
        if (!ok) mbar_wait(sb + BAR_MFULL + b * 8, ph);
        a = wp + b * 8192;
        mp += mc;
        m = lds64(mp);
        w0 = lds128(a); w1 = lds128(a + 1024); w2 = lds128(a + 2048);
      }
      fma8(acc, w3, m3);
      mbar_arrive_warp(sb + BAR_OA);
      float* yacc = gs->y[tn] + (fresh_tid() & 127) * 8;
      red_add4(yacc, acc[0], acc[1], acc[2], acc[3]);
      red_add4(yacc + 4, acc[4], acc[5], acc[6], acc[7]);
      PROF(lane == 0 && mw == 0, 25);
      nb_sync(NB_MODW, 128);
      if (mw == 0 && elect()) { fence_release(); red_add(gs->cnt[32], 1); }
      PROF(lane == 0 && mw == 0, 24);
    }
    const unsigned key = lds32(sb + OFF_MISC + 16);
    const int sel = 0xFFFF - (int)(key & 0xFFFF) - tm * 128;
    if (mw == 0 && sel >= 0 && sel < 128) {
      if (elect()) wait_counter(gs->cnt[32], MOD_CTAS);
      __syncwarp();
      const unsigned k16 = key >> 16;
      const float rs = bf_round(sigmoidf_(__uint_as_float(((k16 & 0x8000u) ? (k16 & 0x7FFFu) : (~k16 & 0xFFFFu)) << 16)));
      float4 v = make_float4(0.f, 0.f, 0.f, 0.f);
#pragma unroll 4
      for (int i = 0; i < 8; i++) {
        const float4 u = ld_relaxed_f4(gs->y[i] + tn * 128 + lane * 4);
        v.x += u.x; v.y += u.y; v.z += u.z; v.w += u.w;
      }
      mbar_wait(sb + BAR_X, 0);
      uint2* xp = (uint2*)(smem + OFF_PK + (lane >> 4) * 16384 + sel * 128 + ((((lane >> 1) & 7) ^ (sel & 7)) << 4) + (lane & 1) * 8);
      const uint2 xv = *xp;
      *xp = make_uint2(pack2(bf_lo(xv.x) + bf_round(bf_round(v.x) * rs), bf_hi(xv.x) + bf_round(bf_round(v.y) * rs)),
                       pack2(bf_lo(xv.y) + bf_round(bf_round(v.z) * rs), bf_hi(xv.y) + bf_round(bf_round(v.w) * rs)));
      __syncwarp();
      mbar_arrive_warp(sb + BAR_Y);
    }
  } else {
    asm volatile("setmaxnreg.inc.sync.aligned.u32 224;");
    const int w = warp & 3, wt = tid & 127;
    const int nb_self = NB_WG0 + wg;
    const uint32_t da0 = mkdesc(sb + OFF_RING, 16), db0 = mkdesc(sb + OFF_RING + A_BYTES, 8192);

    if (wg == 1) {
      float s[8] = {0.f, 0.f, 0.f, 0.f, 0.f, 0.f, 0.f, 0.f};
      const uint32_t zero = lds32(sb + OFF_ONES) & 1;
      uint32_t mask = 0xffff0000u;
#pragma unroll 1
      for (int i = 0; i < 4; i++) {
        const uint32_t u = RT_ORD >> i * 4 & 3;
        mbar_wait(sb + BAR_RT + i * 8, 0);
        const uint4 wr = lds128(sb + OFF_KVB + u * 512 + lane * 16), gw = lds128(sb + OFF_KVB + 2048 + u * 512 + lane * 16);
        uint4 xv[4];
#pragma unroll
        for (int r = 0; r < 4; r++) xv[r] = lds128(sb + OFF_PK + i * 8192 + (w * 4 + r) * 512 + lane * 16);
        const float wf[16] = {bf_lo(wr.x), bf_hi(wr.x), bf_lo(wr.y), bf_hi(wr.y), bf_lo(wr.z), bf_hi(wr.z), bf_lo(wr.w), bf_hi(wr.w),
                              bf_lo(gw.x), bf_hi(gw.x), bf_lo(gw.y), bf_hi(gw.y), bf_lo(gw.z), bf_hi(gw.z), bf_lo(gw.w), bf_hi(gw.w)};
#pragma unroll
        for (int r = 0; r < 4; r++) {
          const uint4 xq = xv[r];
          const float xf[8] = {bf_lo(xq.x), __uint_as_float(xq.x & mask), bf_lo(xq.y), bf_hi(xq.y), bf_lo(xq.z), bf_hi(xq.z), bf_lo(xq.w), bf_hi(xq.w)};
#pragma unroll
          for (int j = 0; j < 8; j++) { s[2 * r] = fmaf(xf[j ^ 1], wf[j ^ 1], s[2 * r]); s[2 * r + 1] = fmaf(xf[j ^ 1], wf[8 + (j ^ 1)], s[2 * r + 1]); }
          mask = ((__float_as_uint(s[2 * r]) | __float_as_uint(s[2 * r + 1])) & zero) | 0xffff0000u;
        }
      }
      mbar_arrive_warp(sb + BAR_RTD);
      float v = butterfly8(s, lane, 1);
      PROF_C(wt == 0 && v != 12345.f, 19);
      v += __shfl_xor_sync(~0u, v, 8);
      v = bf_round(v + __shfl_xor_sync(~0u, v, 16));
      const unsigned rb = __float_as_uint(v) >> 16, row = w * 4 + ((lane & 7) >> 1);
      unsigned key = (lane & 1) ? 0u : ((((rb & 0x8000u) ? (~rb & 0xFFFFu) : (rb | 0x8000u)) << 16) | ((15 - row) << 12));
      key = __reduce_max_sync(~0u, key);
      if (lane == 0) sts32(sb + OFF_MISC + w * 4, key);
      if (lane < 8 && (lane & 1)) sts32(sb + OFF_G + row * 4, __float_as_uint(bf_round(sigmoidf_(v))));
      nb_arrive(NB_KEY, 160);
      nb_sync(NB_ORDER_AB, 256);
    }

    uint32_t pq[2][4][4];
    float4* const kvacc = &gs->kv[wg][tn][0][wt];
    {
      float acc[2][96];
      PROF_C(wt == 0, 1 + wg * 8);
#pragma unroll 1
      for (int g = 0; g < 14; g++) {
        const uint32_t s = g & 3;
        const uint32_t da = da0 + s * (STAGE_BYTES >> 4), db = db0 + s * (STAGE_BYTES >> 4);
        mbar_wait(sb + BAR_FULL + s * 8, (g >> 2) & 1);
        PROF_C(wt == 0, 64 + wg * 16 + g);
#pragma unroll
        for (int m = 0; m < 2; m++) {
          wg_fence();
#pragma unroll
          for (int kk = 0; kk < 4; kk++) mma_qkv(acc[m], da + (m * 512 + kk * 2), db + kk * 128, kk ? 1 : g);
          wg_commit();
          if (m == 0) {
            wg_wait<1>();
            if (g) mbar_arrive_warp(sb + BAR_EMPTY + ((g + 3) & 3) * 8);
          }
        }
      }
      auto half_step = [&](int m, int g) {
        wg_fence();
#pragma unroll
        for (int kk = 0; kk < 4; kk++)
          mma_qkv(acc[m], da0 + ((g & 3) * (STAGE_BYTES >> 4) + m * 512 + kk * 2), db0 + ((g & 3) * (STAGE_BYTES >> 4) + kk * 128), 1);
        wg_commit();
      };
#pragma unroll
      for (int g = 14; g < 16; g++) {
        mbar_wait(sb + BAR_FULL + (g & 3) * 8, 1);
        PROF_C(wt == 0, 64 + wg * 16 + g);
        half_step(0, g);
        if (g == 14) { wg_wait<1>(); mbar_arrive_warp(sb + BAR_EMPTY + ((g + 3) & 3) * 8); }
      }
      half_step(1, 14);
      half_step(1, 15);
      if (wg == 0) nb_arrive(NB_ORDER_AB, 256);
      mbar_wait(sb + BAR_IDX, 0);
      if (wg == 1) nb_sync(NB_STG, 256);
      wg_wait<2>();
      PROF_C(wt == 0, 3 + wg * 8);

      const uint32_t st_row = (uint32_t)(w * 16 + (lane & 15)) * 128;
      float c[36];
      const uint32_t dk = mkdesc(sb + OFF_PK, 16), dv = mkdesc(sb + OFF_V, OFF_ONES - OFF_V);
      uint32_t l2k[8 + PA];
#pragma unroll
      for (int u = 0; u < PA; u++) l2k[u] = 0x3FB8AA3Bu;
#pragma unroll
      for (int u = 0; u < 8; u++) {
        const int m = u >> 2, j = u & 3;
        const uint32_t a = sb + m * 8192 + st_row + ((((lane >> 4) + 2 * j) ^ (lane & 7)) << 4);
        const float* k = &acc[m][32 + 8 * j];
        const float l = __uint_as_float(l2k[u]);
        if (u == M1) {
          wg_wait<1>();
          mbar_arrive_warp(sb + BAR_EMPTY + 2 * 8);
        }
        if (u == MM) {
          wg_wait<0>();
          mbar_arrive_warp(sb + BAR_EMPTY + 3 * 8);
        }
        const float* v = &acc[m][64 + 8 * j];
        stsm4(a + OFF_V, pack2(v[0], v[1]), pack2(v[2], v[3]), pack2(v[4], v[5]), pack2(v[6], v[7]));
        const uint32_t r0 = phi2(k[0], k[1], l), r1 = phi2(k[2], k[3], l), r2 = phi2(k[4], k[5], l), r3 = phi2(k[6], k[7], l);
        stsm4(a + OFF_PK, r0, r1, r2, r3);
        if (u + PA < 8) l2k[u + PA] = lds32(sb + OFF_MISC + 20);
      }
      fence_async_smem();
      nb_sync(nb_self, 128);
      PROF_C(wt == 0, 8 + wg * 8);
      wg_fence();
#pragma unroll
      for (int kk = 0; kk < 8; kk++) mma_ktv(c, dk + kk * 128, dv + (kk * 128 - (kk << 23)), kk ? 1 : 0);
      wg_commit();
      if (wg == 1) nb_arrive(NB_ORDER_BO, 256);
      auto reduce = [&](float4* dst, int gap) {
        wg_wait<0>();
        PROF_C(wt == 0, 4 + wg * 8);
        float u[18];
#pragma unroll
        for (int i = 0; i < 16; i++) u[i] = w >= 2 ? c[16 + i] : c[i];
        u[16] = __shfl_down_sync(~0u, u[15], 1);
        u[17] = lane & 2 ? c[34] : c[32];
#pragma unroll
        for (int i = 0; i < 5; i++) {
          if (gap && i) __nanosleep(gap);
          red_add4(dst + i * 128, u[3 * i], u[3 * i + 1], u[3 * i + 2], i < 3 && !(lane & 1) ? u[i == 0 ? 15 : i == 1 ? 17 : 16] : 1.f);
        }
      };
      const uint32_t zero = lds32(sb + OFF_ONES) & 1;
      if (wg) reduce(kvacc, 0);
      const float l2e = __uint_as_float(lds32(sb + OFF_MISC + 20));
      uint32_t dep = 0;
#pragma unroll
      for (int u = 0; u < 8; u++) {
#pragma unroll
        for (int i = 0; i < 4; i++) dep |= pq[u >> 2][u & 3][i] = phi2(acc[u >> 2][8 * (u & 3) + 2 * i], acc[u >> 2][8 * (u & 3) + 2 * i + 1], l2e);
      }
      float4* const kvp = kvacc + (dep & zero);
      if (!wg) reduce(kvp, RED_SLEEP);
      PROF_C(wt == 0 && kvp == kvacc, 34 + wg * 2);
      for (int tries = wg ? 0 : 9;; tries++) {
        if (tries > RETRY)
          while (ld_relaxed((const unsigned*)&(kvp - lane)[NV * 128 - 128 + 31].w) != 0x41800000u) __nanosleep(wg ? KV_SLEEP : KV_SLEEP_A);
        float4 kv[NV];
#pragma unroll
        for (int i = 0; i < NV; i++) kv[i] = ld_relaxed_f4(kvp + i * 128);
        const uint32_t kb = sb + OFF_KVB + (w >> 1) * 2560 + (w & 1) * 256;
        const uint32_t ka = kb + (lane >> 4) * 512 + (lane & 15) * 16;
        stsm4(ka, pack2(kv[0].x, kv[0].y), pack2(kv[0].z, kv[1].x), pack2(kv[1].y, kv[1].z), pack2(kv[2].x, kv[2].y));
        const uint32_t zz = pack2(kv[1].w, kv[1].w);
        if (!(lane & 1)) sts128(kb + 2048 + (lane & 2) * 64 + (lane >> 2) * 16, zz, zz, zz, zz);
        const float u15 = __shfl_up_sync(~0u, kv[2].w, 1);
        stsm4(ka + 1024, pack2(kv[2].z, kv[3].x), pack2(kv[3].y, kv[3].z), pack2(kv[4].x, kv[4].y), pack2(kv[4].z, lane & 1 ? u15 : kv[0].w));
        const bool ok = !(lane & 1) || kv[0].w + kv[1].w + kv[2].w + kv[3].w + kv[4].w == 80.f;
        if (__all_sync(~0u, ok)) { PROF_V(wg && lane == 0, 40 + w, tries * 100 + 2); break; }
      }
    }
    {
      PROF_C(wt == 0, 5 + wg * 8);
      fence_async_smem();
      nb_sync(nb_self, 128);
      float o[2][2][20];
      const uint32_t dz = mkdesc(sb + OFF_KVB, 128);
      wg_fence();
#pragma unroll
      for (int m = 0; m < 2; m++) {
#pragma unroll
        for (int h = 0; h < 2; h++)
#pragma unroll
          for (int kk = 0; kk < 2; kk++) mma_qkvz(o[m][h], pq[m][2 * h + kk], dz + (h * 160 + kk * 16), kk);
        wg_commit();
      }
      const uint32_t tmask = (lane & 3) == (lane >> 3), tbit = lds32(sb + OFF_MISC + 24) & tmask;
      float gr[2][2], sc[4];
#pragma unroll
      for (int i = 0; i < 4; i++) gr[i >> 1][i & 1] = __uint_as_float(lds32(sb + OFF_G + ((i >> 1) * 64 + (i & 1) * 8 + w * 16 + (lane >> 2)) * 4));
      if (wg == 1) {
        mbar_arrive_warp(sb + BAR_OST);
        mbar_wait(sb + BAR_OA, 0);
      }
      const uint32_t os = sb + (wg ? OFF_MOD : OFF_PK) + w * 2048;
      uint8_t* const og = (uint8_t*)gs->o[tm][wg * 8 + tn] + w * 2048;
#pragma unroll
      for (int m = 0; m < 2; m++) {
        if (m == 0) wg_wait<1>();
        if (m == 0) PROF_C(wt == 0, 6 + wg * 8);
#pragma unroll
        for (int h = 0; h < 2; h++) {
          const float* oo = o[m][h];
          uint32_t pin = 0;
          if (!m && h) {
            wg_wait<0>();
#pragma unroll
            for (int i = 0; i < 4; i++) pin |= __float_as_uint(sc[i] = gr[1][i & 1] * rcp(o[1][i >> 1][16 + (i & 1) * 2] + 1e-6f));
            pin &= __float_as_uint(gr[0][0]) & 16;
          }
          const float s0 = m ? sc[2 * h] : gr[m][0] * rcp(oo[16] + 1e-6f), s1 = m ? sc[2 * h + 1] : gr[m][1] * rcp(oo[18] + 1e-6f);
#pragma unroll
          for (int j = 0; j < 2; j++)
            stsm4(os + m * 8192 + (lane & 15) * 128 + ((((lane >> 4) + 4 * h + 2 * j) ^ (lane & 7)) << 4) + (j ? pin : 0),
                  (pack2(oo[8 * j] * s0, oo[8 * j + 1] * s0) & ~tmask) | tbit, (pack2(oo[8 * j + 2] * s1, oo[8 * j + 3] * s1) & ~tmask) | tbit,
                  pack2(oo[8 * j + 4] * s0, oo[8 * j + 5] * s0), pack2(oo[8 * j + 6] * s1, oo[8 * j + 7] * s1));
        }
        fence_async_smem();
        __syncwarp();
        if (elect()) bulk_store(og + m * 8192, os + m * 8192, 2048);
      }
      if (elect()) {
        bulk_commit();
        if (wg) mbar_arrive(sb + BAR_OWN);
        PROF(wt == 0, 7 + wg * 8);
        if (!wg) red_add(gs->cnt[tm], 1u << tn * 4);
        asm volatile("cp.async.bulk.wait_group.read 0;" ::: "memory");
        PROF(wt == 0, 17 + wg);
        PROF(wt == 96, 38 + wg);
      }
    }

    __syncwarp();
    const uint32_t par = lds32(sb + OFF_MISC + 24), cw = lane * 32 + (lane & 4) * 4 + (lane >> 3) * 4;
    auto check_tile = [&](int g, uint32_t s) {
      const uint32_t a = sb + OFF_RING + s * O_BYTES + w * 2048, fix = sb + BAR_FIX + warp * 8;
      for (;;) {
        const uint32_t u0 = lds32(a + cw), u1 = lds32(a + cw + 1024), u2 = lds32(a + cw + 8192), u3 = lds32(a + cw + 9216);
        if (__all_sync(~0u, !(mism(mism(u0, u1, par), mism(u2, u3, par), 0) & 1))) break;
        PROF_V(lane == 0, 44 + g, 102);
        const int slab = g < OWN ? g : g < PEER ? g - 1 : g == PEER ? 8 + (tn ^ 1) : g - 10 < (tn & 6) ? g - 2 : g;
        const uint4* src = gs->o[tm][slab] + w * 128;
        const uint32_t ph = !mbar_test(fix, 1);
        fence_async_smem();
        __syncwarp();
        if (elect()) { mbar_expect_tx(fix, 4096); bulk_load(a, src, 2048, fix); bulk_load(a + 8192, src + 512, 2048, fix); }
        mbar_wait(fix, ph);
      }
    };
    if (wg == 1) {
#pragma unroll 1
      for (int g = 10; g < 16; g++) {
        const uint32_t s = g == 15 ? 0 : g - 10;
        mbar_wait(sb + BAR_LAND + (g - 10) * 8, 0);
        PROF_C(wt == 0, 214 + g);
        check_tile(g, s);
        if (w) nb_arrive(NB_CHK + (g & 1), 128);
        else { nb_sync(NB_CHK + (g & 1), 128); mbar_arrive_warp(sb + BAR_FULL + s * 8); }
        if (g & 1) nb_sync(nb_self, 128);
      }
    } else {
      nb_arrive(NB_STG, 256);
      float acc[2][64];
      mbar_wait(sb + BAR_W31, 0);
#pragma unroll 1
      for (int g = 0; g < PC; g++) { mbar_wait(sb + BAR_EMPTY + g * 8, 1); mbar_wait(sb + BAR_FULL + g * 8, 0); check_tile(g, g); }
      const uint32_t chk = __shfl_sync(~0u, lds32(sb + OFF_MISC + 28), 0);
      nb_sync(NB_ORDER_BO, 256);
      PROF_C(wt == 0, 26);
      uint32_t xr[2][8][4], q[2][2];
      const uint32_t ta = sb + OFF_PK + (uint32_t)(w * 16 + (lane & 15)) * 128;
#pragma unroll 1
      for (int g = 0; g < 13 - TL; g++) {
        const uint32_t r = g * 52 >> 8, s = g - r * 5;
        const uint32_t da = da0 + (g == OWN ? 5 : s) * (O_BYTES >> 4), db = db0 + s * (O_BYTES >> 4);
        if (g == OWN) {
          wg_wait<0>();
          mbar_arrive_warp(sb + BAR_EMPTY + (OWN + 4) % 5 * 8);
          mbar_wait(sb + BAR_OWN, 0);
        }
        mbar_wait(sb + BAR_FULL + s * 8, r & 1);
        if (chk >> g & 1) check_tile(g, s);
        PROF_C(wt == 0, 96 + g);
        wg_fence();
#pragma unroll
        for (int kk = 0; kk < 4; kk++)
#pragma unroll
          for (int m = 0; m < 2; m++) mma_out(acc[m], da + (m * 512 + kk * 2), db + kk * 128, kk ? 1 : g);
        wg_commit();
        wg_wait<1>();
        if (~(1 | 1 << OWN) >> g & 1) mbar_arrive_warp(sb + BAR_EMPTY + (s ? s - 1 : 4) * 8);
      }
      mbar_wait(sb + BAR_X, 0);
      if (((0xFFFF - (lds32(sb + OFF_MISC + 16) & 0xFFFF)) >> 7) == tm) mbar_wait(sb + BAR_Y, 0);
#pragma unroll
      for (int u = 0; u < 4; u++) {
        const int m = u >> 1, g = 13 - TL + u;
        const float g1 = 1.f - __uint_as_float(lds32(sb + OFF_G + (m * 64 + w * 16 + (u & 1) * 8 + (lane >> 2)) * 4));
        q[m][u & 1] = pack2(g1, g1);
#pragma unroll
        for (int j = 0; j < 4; j++) ldsm4(ta + (u & 1) * 16384 + m * 8192 + ((((lane >> 4) + 2 * j) ^ (lane & 7)) << 4), xr[m][(u & 1) * 4 + j]);
        if (u == 3) break;
        mbar_wait(sb + BAR_FULL + g % 5 * 8, g / 5 & 1);
        PROF_C(wt == 0, 96 + g);
        wg_fence();
#pragma unroll
        for (int kk = 0; kk < 4; kk++)
#pragma unroll
          for (int mm = 0; mm < 2; mm++)
            mma_out(acc[mm], da0 + (g % 5 * (O_BYTES >> 4) + mm * 512 + kk * 2), db0 + (g % 5 * (O_BYTES >> 4) + kk * 128), 1);
        wg_commit();
        wg_wait<1>();
        if (g <= 11) mbar_arrive_warp(sb + BAR_EMPTY + (g + 4) % 5 * 8);
      }
      auto half_step = [&](int m, int g) {
        if (m == 0) { mbar_wait(sb + BAR_FULL + g % 5 * 8, g / 5 & 1); PROF_C(wt == 0, 96 + g); wg_fence(); }
#pragma unroll
        for (int kk = 0; kk < 4; kk++)
          mma_out(acc[m], da0 + (g % 5 * (O_BYTES >> 4) + m * 512 + kk * 2), db0 + (g % 5 * (O_BYTES >> 4) + kk * 128), 1);
      };
      auto stage = [&](int m, int j0, int j1) {
#pragma unroll
        for (int j = j0; j < j1; j++) {
          const float* v = &acc[m][8 * j];
          stsm4(ta + (j >> 2) * 16384 + m * 8192 + ((((lane >> 4) + 2 * (j & 3)) ^ (lane & 7)) << 4),
                fma_bf2(xr[m][j][0], q[m][0], pack2(v[0], v[1])), fma_bf2(xr[m][j][1], q[m][1], pack2(v[2], v[3])),
                fma_bf2(xr[m][j][2], q[m][0], pack2(v[4], v[5])), fma_bf2(xr[m][j][3], q[m][1], pack2(v[6], v[7])));
        }
      };
      auto leave_tma = [&](int m, int h) {
        fence_async_smem();
        __syncwarp();
        if (elect()) tma2d_store(&p.out, sb + OFF_PK + h * 16384 + m * 8192 + w * 2048, tn * 128 + h * 64, tm * 128 + m * 64 + w * 16);
      };
      auto leave = [&](int m, int h) {
        __syncwarp();
        const uint32_t r = lane >> 3;
        uint4 v[4];
#pragma unroll
        for (int i = 0; i < 4; i++) v[i] = lds128(sb + OFF_PK + h * 16384 + m * 8192 + w * 2048 + (r + 4 * i) * 128 + (((lane ^ (r + 4 * i)) & 7) << 4));
        char* const dst = (char*)pout + (size_t)(tm * 128 + m * 64 + w * 16 + r) * (D_ * 2) + tn * 256 + h * 128 + (lane & 7) * 16;
#pragma unroll
        for (int i = 0; i < 4; i++) asm volatile("st.global.v4.u32 [%0], {%1, %2, %3, %4};" ::"l"(dst + i * 4 * D_ * 2), "r"(v[i].x), "r"(v[i].y), "r"(v[i].z), "r"(v[i].w) : "memory");
      };
#pragma unroll
      for (int g = 16 - TL; g < 16; g++) half_step(0, g);
      wg_commit();
#pragma unroll
      for (int g = 16 - TL; g < 16; g++) half_step(1, g);
      wg_commit();
      mbar_arrive_warp(sb + BAR_DONE);
      wg_wait<1>();
      PROF(wt == 0, 35);
      stage(0, 0, 4);
      leave_tma(0, 0);
      stage(0, 4, 8);
      leave_tma(0, 1);
      if (elect()) bulk_commit();
      PROF(wt == 0, 33);
      wg_wait<0>();
      PROF(wt == 0, 31);
#pragma unroll
      for (int h = 0; h < 2; h++) { stage(1, 4 * h, 4 * h + 4); leave(1, h); }
      if (elect()) asm volatile("cp.async.bulk.wait_group.read 0;" ::: "memory");
      PROF(wt == 0, 32);
    }
  }
}

typedef CUresult (*EncodeFn)(CUtensorMap*, CUtensorMapDataType, cuuint32_t, void*, const cuuint64_t*, const cuuint64_t*, const cuuint32_t*,
                             const cuuint32_t*, CUtensorMapInterleave, CUtensorMapSwizzle, CUtensorMapL2promotion, CUtensorMapFloatOOBfill);

void encode(EncodeFn fn, CUtensorMap* m, const void* ptr, int rank, const cuuint64_t* dims, const cuuint64_t* strides, const cuuint32_t* box,
            CUtensorMapSwizzle sw, CUtensorMapDataType dt = CU_TENSOR_MAP_DATA_TYPE_BFLOAT16) {
  const cuuint32_t es[3] = {1, 1, 1};
  fn(m, dt, rank, const_cast<void*>(ptr), dims, strides, box, es, CU_TENSOR_MAP_INTERLEAVE_NONE, sw,
     CU_TENSOR_MAP_L2_PROMOTION_L2_128B, CU_TENSOR_MAP_FLOAT_OOB_FILL_NONE);
}

}

extern "C" void kernel_launch(void* const* d_in, const int* in_sizes, int n_in, void* d_out, int out_size) {
  (void)in_sizes; (void)n_in; (void)out_size;
  EncodeFn fn = nullptr;
  cudaDriverEntryPointQueryResult qr;
  cudaGetDriverEntryPoint("cuTensorMapEncodeTiled", (void**)&fn, cudaEnableDefault, &qr);

  Params p;
  {
    const cuuint64_t dims[2] = {D_, S_}, str[1] = {D_ * 2};
    const cuuint32_t box[2] = {64, 128}, box_st[2] = {64, 16}, box_r[2] = {256, 16};
    encode(fn, &p.xr, d_in[0], 2, dims, str, box_r, CU_TENSOR_MAP_SWIZZLE_NONE);
    encode(fn, &p.x, d_in[0], 2, dims, str, box, CU_TENSOR_MAP_SWIZZLE_128B);
    encode(fn, &p.out, d_out, 2, dims, str, box_st, CU_TENSOR_MAP_SWIZZLE_128B);
  }
  {
    const cuuint64_t dims[3] = {D_, D_, 3}, str[2] = {3 * D_ * 2, D_ * 2};
    const cuuint32_t box[3] = {64, 64, 3};
    encode(fn, &p.w, d_in[1], 3, dims, str, box, CU_TENSOR_MAP_SWIZZLE_128B);
  }
  {
    const cuuint64_t dims[3] = {64, D_, D_ / 64}, str[2] = {D_ * 2, 128};
    const cuuint32_t box[3] = {64, 64, 2};
    encode(fn, &p.wo, d_in[2], 3, dims, str, box, CU_TENSOR_MAP_SWIZZLE_128B);
  }
  {
    const cuuint64_t dims[3] = {F_, D_ / 4, 4}, str[2] = {F_ * 8, F_ * 2};
    const cuuint32_t box[3] = {32, 16, 4};
    encode(fn, &p.gate, d_in[5], 3, dims, str, box, CU_TENSOR_MAP_SWIZZLE_NONE);
    encode(fn, &p.up, d_in[6], 3, dims, str, box, CU_TENSOR_MAP_SWIZZLE_NONE);
  }
  {
    const cuuint64_t dims[3] = {D_ / 4, F_, 2}, str[2] = {D_ * 2, D_};
    const cuuint32_t box[3] = {256, 4, 2};
    encode(fn, &p.down, d_in[7], 3, dims, str, box, CU_TENSOR_MAP_SWIZZLE_NONE, CU_TENSOR_MAP_DATA_TYPE_UINT32);
  }
  void* gs = nullptr;
  cudaGetSymbolAddress(&gs, g_scratch);
  typedef const __nv_bfloat16* bp;
  int dev = 0, sms = 0;
  cudaGetDevice(&dev);
  cudaDeviceGetAttribute(&sms, cudaDevAttrMultiProcessorCount, dev);
  const bool by_sm = BYSM && sms == NGRID;
  const auto kernel = by_sm ? fused_kernel<true> : fused_kernel<false>;
  cudaFuncSetAttribute(kernel, cudaFuncAttributeMaxDynamicSharedMemorySize, SMEM_BYTES);
  kernel<<<by_sm ? NGRID : NCTA, NTHREADS, SMEM_BYTES, cudaStreamPerThread>>>((bp)d_in[0], (Scratch*)gs, (bp)d_in[5], (bp)d_in[6], (bp)d_in[4], (bp)d_in[8], p, d_out);
}
```

```cpp
#include <cuda_runtime.h>
#include <cuda.h>
#include <cuda_bf16.h>
#include <stdint.h>
#include <stddef.h>

namespace {

constexpr int S_ = 2048, D_ = 1024, F_ = 3584;
constexpr int NCTA = 128, NGRID = 132, NTHREADS = 512;
constexpr int MOD_CTAS = F_ / 32;

#define PC 2
#define PRE 2
#define ST1 700
#define RT_G0 2
#define RT_ORD 0x1032
#define RT_SLEEP 500
#define PF_MOD 6
#define MOD_START 9
#define MM 4
#define PA 6
#define RED_SLEEP 32
#define RETRY 1
#define KV_SLEEP_A 128
#define KV_SLEEP 50
#define OWN 5
#define TL 3
#define NOMOD 5
#define FSL 256
#define GMK 0x96
#define M1 1
#define PAIRED 1
#define BYSM 1

constexpr uint32_t A_BYTES = 16384, BQ_BYTES = 24576, BO_BYTES = 16384, STAGE_BYTES = A_BYTES + BQ_BYTES, O_BYTES = A_BYTES + BO_BYTES;
constexpr int MOD_BUFS = 3, MOD_BUFS0 = MOD_BUFS + 1;
static_assert(MOD_START + MOD_BUFS0 <= 16, "first FFN round is requested during wave A");
constexpr uint32_t OFF_RING = 0;
constexpr uint32_t OFF_MOD = 4 * STAGE_BYTES;
constexpr uint32_t OFF_PK = OFF_MOD + MOD_BUFS * 8192;
constexpr uint32_t OFF_V = OFF_PK + 16384;
constexpr uint32_t OFF_ONES = OFF_V + 16384;
constexpr uint32_t OFF_KVB = OFF_ONES + 2048;
constexpr uint32_t OFF_XSEL = OFF_KVB + 5120;
constexpr uint32_t OFF_G = OFF_XSEL + 2048;
constexpr uint32_t OFF_PART = OFF_G + 512;
constexpr uint32_t OFF_MISC = OFF_PART + 576;
constexpr uint32_t OFF_BAR = OFF_MISC + 32;
constexpr uint32_t BAR_FULL = OFF_BAR, BAR_EMPTY = OFF_BAR + 40, BAR_RTD = OFF_BAR + 80, BAR_Y = OFF_BAR + 88, BAR_DONE = OFF_BAR + 96,
                   BAR_X = OFF_BAR + 104, BAR_OA = OFF_BAR + 112, BAR_OWN = OFF_BAR + 120, BAR_OST = OFF_BAR + 128, BAR_PA = OFF_BAR + 136,
                   BAR_W31 = OFF_BAR + 144, BAR_MFULL = OFF_BAR + 152, BAR_MEMPTY = BAR_MFULL + MOD_BUFS0 * 8,
                   BAR_IDX = BAR_MEMPTY + MOD_BUFS * 8;
constexpr uint32_t SMEM_BYTES = OFF_BAR + 384;
static_assert(SMEM_BYTES <= 232448, "smem");

constexpr uint32_t BAR_LAND = OFF_BAR + 256, BAR_FIX = BAR_LAND + 64;
constexpr uint32_t BAR_RT = BAR_FIX;
static_assert(TL == 3 && PRE == 2 && BAR_IDX - OFF_BAR < 256, "warp w initialises barriers 2w and 2w + 1");
constexpr __host__ __device__ uint64_t bar_counts(int first) {
  uint64_t r = 0;
  for (uint32_t i = 0; i < 16; i++) {
    const uint32_t b = OFF_BAR + (first + i) * 8;
    const uint64_t c = b < BAR_EMPTY ? 2 : b == BAR_IDX ? 5 : b == BAR_Y || b == BAR_X || (b >= BAR_PA && b < BAR_MEMPTY) ? 1 : 4;
    r |= c << i * 4;
  }
  return r;
}

constexpr int NB_WG0 = 1, NB_ORDER_AB = 3, NB_ORDER_BO = 4, NB_STG = 5, NB_MODW = 6, NB_KEY = 7, NB_CHK = 8;

constexpr int NV = 5, NCLR = NV * 4 + 5;
struct Scratch {
  float4 kv[2][8][NV][128];
  float y[8][D_];
  unsigned cnt[64][32];
  unsigned gslot[S_];
  unsigned rslot[8][NCTA];
  unsigned spare[128];
  unsigned block[NCTA];
  uint4 o[16][16][1024];
};
static_assert(offsetof(Scratch, gslot) == NCTA * NCLR * 64, "clear size");
__device__ __align__(1024) Scratch g_scratch;

#define PROF(cond, i) do {} while (0)
#define PROF_C(cond, i) do {} while (0)
#define PROF_P(cond, i) do {} while (0)
#define PROF_V(cond, i, v) do {} while (0)

__device__ __forceinline__ void mbar_init(uint32_t bar, int cnt) { asm volatile("mbarrier.init.shared::cta.b64 [%0], %1;" ::"r"(bar), "r"(cnt)); }
__device__ __forceinline__ void mbar_expect_tx(uint32_t bar, uint32_t bytes) { asm volatile("mbarrier.arrive.expect_tx.shared::cta.b64 _, [%0], %1;" ::"r"(bar), "r"(bytes) : "memory"); }
__device__ __forceinline__ void mbar_arrive(uint32_t bar) { asm volatile("mbarrier.arrive.shared::cta.b64 _, [%0];" ::"r"(bar) : "memory"); }
__device__ __forceinline__ uint32_t peer_addr(uint32_t a) {
  uint32_t r;
  asm volatile("{\n.reg .u32 c;\nmov.u32 c, %%cluster_ctarank;\nxor.b32 c, c, 1;\nmapa.shared::cluster.u32 %0, %1, c;\n}" : "=r"(r) : "r"(a));
  return r;
}
__device__ __forceinline__ void mbar_arrive_peer(uint32_t bar) { asm volatile("mbarrier.arrive.shared::cluster.b64 _, [%0];" ::"r"(bar) : "memory"); }
__device__ __forceinline__ uint32_t mism(uint32_t a, uint32_t b, uint32_t p) {
  uint32_t r; asm("lop3.b32 %0, %1, %2, %3, 0x7E;" : "=r"(r) : "r"(a), "r"(b), "r"(p)); return r;
}
__device__ __forceinline__ bool elect() {
  uint32_t r;
  asm volatile("{\n.reg .pred p;\nelect.sync _|p, 0xffffffff;\nselp.u32 %0, 1, 0, p;\n}" : "=r"(r));
  return r;
}
__device__ __forceinline__ uint32_t fresh_tid() { uint32_t r; asm volatile("mov.u32 %0, %%tid.x;" : "=r"(r)); return r; }
__device__ __forceinline__ void mbar_arrive_warp(uint32_t bar) {
  asm volatile("{\n.reg .pred p;\nelect.sync _|p, 0xffffffff;\n@p mbarrier.arrive.shared::cta.b64 _, [%0];\n}" ::"r"(bar) : "memory");
}
__device__ __forceinline__ void mbar_wait(uint32_t bar, uint32_t parity) {
  asm volatile("{\n.reg .pred p;\nWAIT_L:\nmbarrier.try_wait.parity.shared::cta.b64 p, [%0], %1;\n@p bra DONE_L;\nbra WAIT_L;\nDONE_L:\n}"
               ::"r"(bar), "r"(parity) : "memory");
}
__device__ __forceinline__ uint32_t mbar_test(uint32_t bar, uint32_t parity) {
  uint32_t ok;
  asm volatile("{\n.reg .pred p;\nmbarrier.test_wait.parity.shared::cta.b64 p, [%1], %2;\nselp.u32 %0, 1, 0, p;\n}" : "=r"(ok) : "r"(bar), "r"(parity) : "memory");
  return ok;
}
constexpr unsigned long long WATCHDOG_NS = 2000000000ull;
__device__ __forceinline__ unsigned long long gtime() { unsigned long long t; asm volatile("mov.u64 %0, %%globaltimer;" : "=l"(t)); return t; }
__device__ __forceinline__ uint32_t clock32() { uint32_t t; asm volatile("mov.u32 %0, %%clock;" : "=r"(t)); return t; }
__device__ __forceinline__ void mbar_wait_bounded(uint32_t bar, uint32_t parity) {
  unsigned long long t0 = 0;
  for (;;) {
    uint32_t ok;
    asm volatile("{\n.reg .pred p;\nmbarrier.try_wait.parity.shared::cta.b64 p, [%1], %2;\nselp.u32 %0, 1, 0, p;\n}" : "=r"(ok) : "r"(bar), "r"(parity) : "memory");
    if (ok) break;
    const unsigned long long t1 = gtime();
    if (t0 == 0) t0 = t1;
    if (t1 - t0 > WATCHDOG_NS) __trap();
  }
}
__device__ __forceinline__ void tma2d(uint32_t dst, const CUtensorMap* m, int c0, int c1, uint32_t bar) {
  asm volatile("cp.async.bulk.tensor.2d.shared::cluster.global.mbarrier::complete_tx::bytes [%0], [%1, {%3, %4}], [%2];"
               ::"r"(dst), "l"(m), "r"(bar), "r"(c0), "r"(c1) : "memory");
}
__device__ __forceinline__ void tma3d(uint32_t dst, const CUtensorMap* m, int c0, int c1, int c2, uint32_t bar) {
  asm volatile("cp.async.bulk.tensor.3d.shared::cluster.global.mbarrier::complete_tx::bytes [%0], [%1, {%3, %4, %5}], [%2];"
               ::"r"(dst), "l"(m), "r"(bar), "r"(c0), "r"(c1), "r"(c2) : "memory");
}
__device__ __forceinline__ void bulk_load(uint32_t dst, const void* src, uint32_t bytes, uint32_t bar) {
  asm volatile("cp.async.bulk.shared::cluster.global.mbarrier::complete_tx::bytes [%0], [%1], %2, [%3];" ::"r"(dst), "l"(src), "r"(bytes), "r"(bar) : "memory");
}
__device__ __forceinline__ void bulk_store(void* dst, uint32_t src, uint32_t bytes) {
  asm volatile("cp.async.bulk.global.shared::cta.bulk_group [%0], [%1], %2;" ::"l"(dst), "r"(src), "r"(bytes) : "memory");
}
__device__ __forceinline__ void bulk_push(uint32_t dst, uint32_t src, uint32_t bytes, uint32_t bar) {
  asm volatile("cp.async.bulk.shared::cluster.shared::cta.mbarrier::complete_tx::bytes [%0], [%1], %2, [%3];" ::"r"(dst), "r"(src), "r"(bytes), "r"(bar) : "memory");
}
__device__ __forceinline__ void bulk_commit() { asm volatile("cp.async.bulk.commit_group;" ::: "memory"); }
__device__ __forceinline__ void bulk_prefetch(const void* p, uint32_t bytes) {
  asm volatile("cp.async.bulk.prefetch.L2.global [%0], %1;" ::"l"(p), "r"(bytes) : "memory");
}
__device__ __forceinline__ void tma2d_store(const CUtensorMap* m, uint32_t src, int c0, int c1) {
  asm volatile("cp.async.bulk.tensor.2d.global.shared::cta.bulk_group [%0, {%2, %3}], [%1];" ::"l"(m), "r"(src), "r"(c0), "r"(c1) : "memory");
}
__device__ __forceinline__ void wg_fence() { asm volatile("wgmma.fence.sync.aligned;" ::: "memory"); }
__device__ __forceinline__ void wg_commit() { asm volatile("wgmma.commit_group.sync.aligned;" ::: "memory"); }
template <int N> __device__ __forceinline__ void wg_wait() { asm volatile("wgmma.wait_group.sync.aligned %0;" ::"n"(N) : "memory"); }
__device__ __forceinline__ void fence_async_smem() { asm volatile("fence.proxy.async.shared::cta;" ::: "memory"); }
__device__ __forceinline__ void fence_release() { asm volatile("fence.release.gpu;" ::: "memory"); }
__device__ __forceinline__ void fence_acquire() { asm volatile("fence.acquire.gpu;" ::: "memory"); }
__device__ __forceinline__ void nb_sync(int id, int n) { asm volatile("bar.sync %0, %1;" ::"r"(id), "r"(n) : "memory"); }
__device__ __forceinline__ void nb_arrive(int id, int n) { asm volatile("bar.arrive %0, %1;" ::"r"(id), "r"(n) : "memory"); }
__device__ __forceinline__ void stsm4(uint32_t addr, uint32_t r0, uint32_t r1, uint32_t r2, uint32_t r3) {
  asm volatile("stmatrix.sync.aligned.m8n8.x4.shared.b16 [%0], {%1, %2, %3, %4};" ::"r"(addr), "r"(r0), "r"(r1), "r"(r2), "r"(r3) : "memory");
}
__device__ __forceinline__ void sts128(uint32_t addr, uint32_t a, uint32_t b, uint32_t c, uint32_t d) {
  asm volatile("st.shared.v4.b32 [%0], {%1, %2, %3, %4};" ::"r"(addr), "r"(a), "r"(b), "r"(c), "r"(d) : "memory");
}
__device__ __forceinline__ uint32_t pack2(float lo, float hi) {
  uint32_t r; asm("cvt.rn.bf16x2.f32 %0, %1, %2;" : "=r"(r) : "f"(hi), "f"(lo)); return r;
}
__device__ __forceinline__ float bf_lo(uint32_t v) { return __uint_as_float(v << 16); }
__device__ __forceinline__ float bf_hi(uint32_t v) { return __uint_as_float(v & 0xffff0000u); }
__device__ __forceinline__ float bf_round(float v) { return __bfloat162float(__float2bfloat16_rn(v)); }
__device__ __forceinline__ void ldsm4(uint32_t addr, uint32_t (&r)[4]) {
  asm volatile("ldmatrix.sync.aligned.m8n8.x4.shared.b16 {%0, %1, %2, %3}, [%4];" : "=r"(r[0]), "=r"(r[1]), "=r"(r[2]), "=r"(r[3]) : "r"(addr) : "memory");
}
__device__ __forceinline__ uint4 lds128(uint32_t addr) {
  uint4 v; asm volatile("ld.volatile.shared.v4.u32 {%0, %1, %2, %3}, [%4];" : "=r"(v.x), "=r"(v.y), "=r"(v.z), "=r"(v.w) : "r"(addr) : "memory"); return v;
}
__device__ __forceinline__ uint2 lds64(uint32_t addr) { uint2 v; asm volatile("ld.volatile.shared.v2.u32 {%0, %1}, [%2];" : "=r"(v.x), "=r"(v.y) : "r"(addr) : "memory"); return v; }
__device__ __forceinline__ uint32_t lds32(uint32_t addr) { uint32_t v; asm volatile("ld.volatile.shared.u32 %0, [%1];" : "=r"(v) : "r"(addr) : "memory"); return v; }
__device__ __forceinline__ void sts32(uint32_t addr, uint32_t v) { asm volatile("st.shared.u32 [%0], %1;" ::"r"(addr), "r"(v) : "memory"); }
__device__ __forceinline__ uint32_t fma_bf2(uint32_t a, uint32_t b, uint32_t c) { uint32_t r; asm("fma.rn.bf16x2 %0, %1, %2, %3;" : "=r"(r) : "r"(a), "r"(b), "r"(c)); return r; }
__device__ __forceinline__ unsigned ld_relaxed(const unsigned* p) { unsigned v; asm volatile("ld.relaxed.gpu.global.u32 %0, [%1];" : "=r"(v) : "l"(p) : "memory"); return v; }
__device__ __forceinline__ void st_relaxed(unsigned* p, unsigned v) { asm volatile("st.relaxed.gpu.global.u32 [%0], %1;" ::"l"(p), "r"(v) : "memory"); }
__device__ __forceinline__ uint4 ld_relaxed4(const void* p) {
  uint4 v; asm volatile("ld.relaxed.gpu.global.v4.u32 {%0, %1, %2, %3}, [%4];" : "=r"(v.x), "=r"(v.y), "=r"(v.z), "=r"(v.w) : "l"(p) : "memory"); return v;
}
__device__ __forceinline__ float4 ld_relaxed_f4(const void* p) {
  float4 v; asm volatile("ld.relaxed.gpu.global.v4.f32 {%0, %1, %2, %3}, [%4];" : "=f"(v.x), "=f"(v.y), "=f"(v.z), "=f"(v.w) : "l"(p) : "memory"); return v;
}
__device__ __forceinline__ void red_add4(void* p, float a, float b, float c, float d) {
  asm volatile("red.relaxed.gpu.global.add.v4.f32 [%0], {%1, %2, %3, %4};" ::"l"(p), "f"(a), "f"(b), "f"(c), "f"(d) : "memory");
}
__device__ __forceinline__ void red_add(unsigned* p, unsigned v) { asm volatile("red.relaxed.gpu.global.add.u32 [%0], %1;" ::"l"(p), "r"(v) : "memory"); }
__device__ __forceinline__ void wait_counter(const unsigned* p, unsigned target) {
  while (ld_relaxed(p) < target) __nanosleep(32);
  fence_acquire();
}
__device__ __forceinline__ float rcp(float v) { float r; asm("rcp.approx.ftz.f32 %0, %1;" : "=f"(r) : "f"(v)); return r; }
__device__ __forceinline__ float sigmoidf_(float v) { return rcp(1.f + __expf(-v)); }
__device__ __forceinline__ uint32_t phi2(float a, float b, float l2e = 1.4426950408889634f) {
  float ea, eb;
  asm("ex2.approx.ftz.f32 %0, %1;" : "=f"(ea) : "f"(a * l2e));
  asm("ex2.approx.ftz.f32 %0, %1;" : "=f"(eb) : "f"(b * l2e));
  uint32_t t = pack2(a, b), e = pack2(ea, eb), r;
  asm("max.NaN.bf16x2 %0, %0, %1;" : "+r"(t) : "r"(0x35863586u));
  asm("min.bf16x2 %0, %0, %1;" : "+r"(e) : "r"(0x3F803F80u));
  asm("add.rn.bf16x2 %0, %1, %2;" : "=r"(r) : "r"(t), "r"(e));
  return r;
}
__device__ __forceinline__ uint32_t mkdesc(uint32_t addr, uint32_t lbo) { return ((addr & 0x3FFFF) >> 4) | ((lbo >> 4) << 16); }

__device__ __forceinline__ void mma_qkv(float (&d)[96], uint32_t da, uint32_t db, int sc) {
  asm volatile("{\n.reg .pred p;\n.reg .b64 da, db;\nmov.b64 da, {%96, 0x40000040};\nmov.b64 db, {%97, 0x40000040};\nsetp.ne.b32 p, %98, 0;\n"
    "wgmma.mma_async.sync.aligned.m64n192k16.f32.bf16.bf16 "
    "{%0,%1,%2,%3,%4,%5,%6,%7,%8,%9,%10,%11,%12,%13,%14,%15,%16,%17,%18,%19,%20,%21,%22,%23,"
    "%24,%25,%26,%27,%28,%29,%30,%31,%32,%33,%34,%35,%36,%37,%38,%39,%40,%41,%42,%43,%44,%45,%46,%47,"
    "%48,%49,%50,%51,%52,%53,%54,%55,%56,%57,%58,%59,%60,%61,%62,%63,%64,%65,%66,%67,%68,%69,%70,%71,"
    "%72,%73,%74,%75,%76,%77,%78,%79,%80,%81,%82,%83,%84,%85,%86,%87,%88,%89,%90,%91,%92,%93,%94,%95}, "
    "da, db, p, 1, 1, 0, 1;\n}\n"
    : "+f"(d[0]), "+f"(d[1]), "+f"(d[2]), "+f"(d[3]), "+f"(d[4]), "+f"(d[5]), "+f"(d[6]), "+f"(d[7]),
      "+f"(d[8]), "+f"(d[9]), "+f"(d[10]), "+f"(d[11]), "+f"(d[12]), "+f"(d[13]), "+f"(d[14]), "+f"(d[15]),
      "+f"(d[16]), "+f"(d[17]), "+f"(d[18]), "+f"(d[19]), "+f"(d[20]), "+f"(d[21]), "+f"(d[22]), "+f"(d[23]),
      "+f"(d[24]), "+f"(d[25]), "+f"(d[26]), "+f"(d[27]), "+f"(d[28]), "+f"(d[29]), "+f"(d[30]), "+f"(d[31]),
      "+f"(d[32]), "+f"(d[33]), "+f"(d[34]), "+f"(d[35]), "+f"(d[36]), "+f"(d[37]), "+f"(d[38]), "+f"(d[39]),
      "+f"(d[40]), "+f"(d[41]), "+f"(d[42]), "+f"(d[43]), "+f"(d[44]), "+f"(d[45]), "+f"(d[46]), "+f"(d[47]),
      "+f"(d[48]), "+f"(d[49]), "+f"(d[50]), "+f"(d[51]), "+f"(d[52]), "+f"(d[53]), "+f"(d[54]), "+f"(d[55]),
      "+f"(d[56]), "+f"(d[57]), "+f"(d[58]), "+f"(d[59]), "+f"(d[60]), "+f"(d[61]), "+f"(d[62]), "+f"(d[63]),
      "+f"(d[64]), "+f"(d[65]), "+f"(d[66]), "+f"(d[67]), "+f"(d[68]), "+f"(d[69]), "+f"(d[70]), "+f"(d[71]),
      "+f"(d[72]), "+f"(d[73]), "+f"(d[74]), "+f"(d[75]), "+f"(d[76]), "+f"(d[77]), "+f"(d[78]), "+f"(d[79]),
      "+f"(d[80]), "+f"(d[81]), "+f"(d[82]), "+f"(d[83]), "+f"(d[84]), "+f"(d[85]), "+f"(d[86]), "+f"(d[87]),
      "+f"(d[88]), "+f"(d[89]), "+f"(d[90]), "+f"(d[91]), "+f"(d[92]), "+f"(d[93]), "+f"(d[94]), "+f"(d[95])
    : "r"(da), "r"(db), "r"(sc));
}

__device__ __forceinline__ void mma_out(float (&d)[64], uint32_t da, uint32_t db, int sc) {
  asm volatile("{\n.reg .pred p;\n.reg .b64 da, db;\nmov.b64 da, {%64, 0x40000040};\nmov.b64 db, {%65, 0x40000040};\nsetp.ne.b32 p, %66, 0;\n"
    "wgmma.mma_async.sync.aligned.m64n128k16.f32.bf16.bf16 "
    "{%0,%1,%2,%3,%4,%5,%6,%7,%8,%9,%10,%11,%12,%13,%14,%15,%16,%17,%18,%19,%20,%21,%22,%23,"
    "%24,%25,%26,%27,%28,%29,%30,%31,%32,%33,%34,%35,%36,%37,%38,%39,%40,%41,%42,%43,%44,%45,%46,%47,"
    "%48,%49,%50,%51,%52,%53,%54,%55,%56,%57,%58,%59,%60,%61,%62,%63}, "
    "da, db, p, 1, 1, 0, 1;\n}\n"
    : "+f"(d[0]), "+f"(d[1]), "+f"(d[2]), "+f"(d[3]), "+f"(d[4]), "+f"(d[5]), "+f"(d[6]), "+f"(d[7]),
      "+f"(d[8]), "+f"(d[9]), "+f"(d[10]), "+f"(d[11]), "+f"(d[12]), "+f"(d[13]), "+f"(d[14]), "+f"(d[15]),
      "+f"(d[16]), "+f"(d[17]), "+f"(d[18]), "+f"(d[19]), "+f"(d[20]), "+f"(d[21]), "+f"(d[22]), "+f"(d[23]),
      "+f"(d[24]), "+f"(d[25]), "+f"(d[26]), "+f"(d[27]), "+f"(d[28]), "+f"(d[29]), "+f"(d[30]), "+f"(d[31]),
      "+f"(d[32]), "+f"(d[33]), "+f"(d[34]), "+f"(d[35]), "+f"(d[36]), "+f"(d[37]), "+f"(d[38]), "+f"(d[39]),
      "+f"(d[40]), "+f"(d[41]), "+f"(d[42]), "+f"(d[43]), "+f"(d[44]), "+f"(d[45]), "+f"(d[46]), "+f"(d[47]),
      "+f"(d[48]), "+f"(d[49]), "+f"(d[50]), "+f"(d[51]), "+f"(d[52]), "+f"(d[53]), "+f"(d[54]), "+f"(d[55]),
      "+f"(d[56]), "+f"(d[57]), "+f"(d[58]), "+f"(d[59]), "+f"(d[60]), "+f"(d[61]), "+f"(d[62]), "+f"(d[63])
    : "r"(da), "r"(db), "r"(sc));
}

__device__ __forceinline__ void mma_ktv(float (&d)[36], uint32_t da, uint32_t db, int sc) {
  asm volatile("{\n.reg .pred p;\n.reg .b64 da, db;\nmov.b64 da, {%36, 0x40000040};\nmov.b64 db, {%37, 0x40000040};\nsetp.ne.b32 p, %38, 0;\n"
    "wgmma.mma_async.sync.aligned.m64n72k16.f32.bf16.bf16 "
    "{%0,%1,%2,%3,%4,%5,%6,%7,%8,%9,%10,%11,%12,%13,%14,%15,%16,%17,%18,%19,%20,%21,%22,%23,"
    "%24,%25,%26,%27,%28,%29,%30,%31,%32,%33,%34,%35}, "
    "da, db, p, 1, 1, 1, 1;\n}\n"
    : "+f"(d[0]), "+f"(d[1]), "+f"(d[2]), "+f"(d[3]), "+f"(d[4]), "+f"(d[5]), "+f"(d[6]), "+f"(d[7]),
      "+f"(d[8]), "+f"(d[9]), "+f"(d[10]), "+f"(d[11]), "+f"(d[12]), "+f"(d[13]), "+f"(d[14]), "+f"(d[15]),
      "+f"(d[16]), "+f"(d[17]), "+f"(d[18]), "+f"(d[19]), "+f"(d[20]), "+f"(d[21]), "+f"(d[22]), "+f"(d[23]),
      "+f"(d[24]), "+f"(d[25]), "+f"(d[26]), "+f"(d[27]), "+f"(d[28]), "+f"(d[29]), "+f"(d[30]), "+f"(d[31]),
      "+f"(d[32]), "+f"(d[33]), "+f"(d[34]), "+f"(d[35])
    : "r"(da), "r"(db), "r"(sc));
}

__device__ __forceinline__ void mma_qkvz(float (&d)[20], const uint32_t (&a)[4], uint32_t db, int sc) {
  asm volatile("{\n.reg .pred p;\n.reg .b64 db;\nmov.b64 db, {%24, 0x20};\nsetp.ne.b32 p, %25, 0;\n"
    "wgmma.mma_async.sync.aligned.m64n40k16.f32.bf16.bf16 "
    "{%0,%1,%2,%3,%4,%5,%6,%7,%8,%9,%10,%11,%12,%13,%14,%15,%16,%17,%18,%19}, "
    "{%20,%21,%22,%23}, db, p, 1, 1, 1;\n}\n"
    : "+f"(d[0]), "+f"(d[1]), "+f"(d[2]), "+f"(d[3]), "+f"(d[4]), "+f"(d[5]), "+f"(d[6]), "+f"(d[7]),
      "+f"(d[8]), "+f"(d[9]), "+f"(d[10]), "+f"(d[11]), "+f"(d[12]), "+f"(d[13]), "+f"(d[14]), "+f"(d[15]),
      "+f"(d[16]), "+f"(d[17]), "+f"(d[18]), "+f"(d[19])
    : "r"(a[0]), "r"(a[1]), "r"(a[2]), "r"(a[3]), "r"(db), "r"(sc));
}

struct Params {
  CUtensorMap x, w, xr, wo, out, gate, up, down;
};

__device__ __forceinline__ void fma8(float (&acc)[8], const uint4& w, float m) {
  acc[0] = fmaf(bf_lo(w.x), m, acc[0]); acc[1] = fmaf(bf_hi(w.x), m, acc[1]);
  acc[2] = fmaf(bf_lo(w.y), m, acc[2]); acc[3] = fmaf(bf_hi(w.y), m, acc[3]);
  acc[4] = fmaf(bf_lo(w.z), m, acc[4]); acc[5] = fmaf(bf_hi(w.z), m, acc[5]);
  acc[6] = fmaf(bf_lo(w.w), m, acc[6]); acc[7] = fmaf(bf_hi(w.w), m, acc[7]);
}
__device__ __forceinline__ float butterfly8(float (&s)[8], int lane, int o) {
#pragma unroll
  for (int k = 1; k < 8; k <<= 1) {
    const bool up = lane & (o * k);
#pragma unroll
    for (int j = 0; j < 4 / k; j++) s[j] = (up ? s[2 * j + 1] : s[2 * j]) + __shfl_xor_sync(~0u, up ? s[2 * j] : s[2 * j + 1], o * k);
  }
  return s[0];
}
constexpr int PEER = 9;
constexpr __host__ __device__ uint32_t step_list() {
  uint32_t r = 0;
  for (int j = PEER - 1; j >= 0; j--) if (j != OWN) r = r << 4 | j % 5 | (j < 5) << 3;
  return r;
}
template <bool BY_SM> struct Tile {
  int sm, tm, tn, mu;
  bool spare;
  __device__ __forceinline__ Tile() {
    if (BY_SM) asm volatile("mov.u32 %0, %%smid;" : "=r"(sm));
    else sm = blockIdx.x + (blockIdx.x >= 120) * 4;
    const int tp = sm >> 1, pr = sm & 1;
    const int v = tp < 32 ? tp : tp < 60 ? (tp * 293 - 928) >> 8 : tp * 8 - 464, g = v & 7, i = v >> 3;
    const int j = i * 11 >> 5, c = i - j * 3;
    tm = (v & 6) * 2 + (c < 2 ? j : 3); tn = (GMK * 4 >> g & 4) + (c < 2 ? c : j) * 2 + pr;
    mu = i == NOMOD ? 112 : g * 14 + (i - (i > NOMOD)) * 2 + pr;
    spare = (tp | 1) == 61;
  }
};

template <bool BY_SM> __global__ void __cluster_dims__(2, 1, 1) __launch_bounds__(NTHREADS, 1)
fused_kernel(const __nv_bfloat16* __restrict__ px, Scratch* gs, void* pout, const __nv_bfloat16* __restrict__ w_r, const __nv_bfloat16* __restrict__ gate_w,
             const __nv_bfloat16* __restrict__ w_gate, const __grid_constant__ Params p, const __nv_bfloat16* __restrict__ w_up) {
  extern __shared__ __align__(1024) uint8_t smem[];
  const uint32_t sb = __shfl_sync(~0u, (uint32_t)__cvta_generic_to_shared(smem), 0);
  const int tid = threadIdx.x, lane = tid & 31;
  const int warp = __shfl_sync(~0u, tid >> 5, 0), wg = warp >> 2;
  const uint32_t t_start = clock32();
  const Tile<BY_SM> tile;
  const int tm = tile.tm, tn = tile.tn, mu = tile.mu, cta = tm * 8 + tn;
  {
    const uint32_t cnt = (uint32_t)((warp & 8 ? bar_counts(16) : bar_counts(0)) >> (warp & 7) * 8);
    if (elect()) mbar_init(sb + OFF_BAR + warp * 16, cnt & 15);
    if (elect()) mbar_init(sb + OFF_BAR + warp * 16 + 8, cnt >> 4 & 15);
    if (elect()) mbar_init(sb + BAR_LAND + warp * 8, 1);
    asm volatile("fence.mbarrier_init.release.cluster;" ::: "memory");
  }
  if (warp == 0 && !tile.spare) {
#pragma unroll
    for (int s = 0; s < PRE; s++) {
      if (elect()) tma3d(sb + OFF_RING + s * STAGE_BYTES + A_BYTES, &p.w, tn * 64, s * 64, 0, sb + BAR_FULL + s * 8);
      if (elect()) tma2d(sb + OFF_RING + s * STAGE_BYTES, &p.x, s * 64, tm * 128, sb + BAR_FULL + s * 8);
      PROF_P(lane == 0, 64 + s);
    }
    if (elect()) {
#pragma unroll
      for (int s = 0; s < PRE; s++) { mbar_expect_tx(sb + BAR_FULL + s * 8, STAGE_BYTES); mbar_arrive(sb + BAR_FULL + s * 8); }
    }
  }
  asm volatile("" ::: "memory");
  if (warp == 5) {
#pragma unroll
    for (int i = 0; i < 4; i++) sts128(sb + OFF_ONES + i * 512 + lane * 16, 0x3F803F80u, 0x3F803F80u, 0x3F803F80u, 0x3F803F80u);
    sts32(sb + OFF_MISC + 20, 0x3FB8AA3Bu);
    fence_async_smem();
  }
  __syncthreads();
  if (tile.spare) {
    if (warp == 0) {
      const unsigned tag = (ld_relaxed(&gs->spare[tile.sm & 3]) + 1) & 0xFFF;
      const unsigned long long t0 = gtime();
      uint4 r4;
      do {
        __nanosleep(2048);
        if (gtime() - t0 > WATCHDOG_NS) __trap();
        r4 = ld_relaxed4(&gs->rslot[tile.sm & 3][lane * 4]);
      } while (!__all_sync(~0u, (((r4.x ^ tag) | (r4.y ^ tag) | (r4.z ^ tag) | (r4.w ^ tag)) & 0xFFF) == 0));
      if (tid == 0) st_relaxed(&gs->spare[tile.sm & 3], tag);
    }
    return;
  }

  if (wg == 3) {
    asm volatile("setmaxnreg.dec.sync.aligned.u32 24;");
    if (warp == 12) {
      mbar_wait(sb + BAR_W31, 0);
      mbar_wait(sb + BAR_IDX, 0);
      const uint32_t lowb = (1u << (tn & 6) * 4) - 1;
      uint32_t slabs = 0x76543210u, steps = step_list();
      const uint4* src = gs->o[tm][0];
      unsigned seen = 0;
#pragma unroll 1
      for (int n = 8; n >= 6; n -= 2) {
#pragma unroll 1
        for (int i = 0; i < n; i++, slabs >>= 4, steps >>= 4) {
          const uint32_t s = steps & 7, full = sb + BAR_FULL + s * 8, need = 4u << (slabs & 7) * 4;
          const uint32_t land = n == 8 ? full : sb + BAR_LAND + i * 8;
          mbar_wait(full + (BAR_EMPTY - BAR_FULL), steps >> 3 & 1);
          PROF(lane == 0 && (!PROFC || n == 6), 224 + i + (n == 6) * 10);
          if (!__all_sync(~0u, seen & need)) {
            while (!__all_sync(~0u, (seen = ld_relaxed(gs->cnt[tm])) & need)) __nanosleep(FSL);
          }
          if (elect()) bulk_load(sb + OFF_RING + s * O_BYTES, src + (slabs & 7) * 1024, A_BYTES, land);
          if (elect()) mbar_expect_tx(land, A_BYTES);
          PROF(lane == 0 && (!PROFC || n == 6), 240 + i + (n == 6) * 10);
        }
        slabs = (0x76543210u & lowb) | (0x765432u & ~lowb);
        steps = 0x0CBA98u;
        src += 8 * 1024;
      }
    } else if (warp == 13) {
      uint32_t full = sb + BAR_FULL + PRE * 8, dst = sb + OFF_RING + PRE * STAGE_BYTES + A_BYTES, c0 = tn * 64, c1 = PRE * 64;
#pragma unroll 1
      for (int g = PRE; g < 32; g++) {
        if (g < 4) while ((int)(clock32() - t_start) < g * ST1) {}
        const bool reuse = (g >> 2) == 4;
        mbar_wait(full + (BAR_EMPTY - BAR_FULL), ((g >> 2) & 1) ^ 1);
        if (!reuse && elect()) tma2d(dst - A_BYTES, &p.x, c1, tm * 128, full);
        if (elect()) tma3d(dst, &p.w, c0, c1, 0, full);
        if (elect()) { mbar_expect_tx(full, reuse ? BQ_BYTES : STAGE_BYTES); mbar_arrive(full); }

        PROF_P(lane == 0, 64 + g);
        const uint32_t i = g - RT_G0;
        if (i < 4 && elect()) {
          mbar_expect_tx(sb + BAR_RT + i * 8, i ? 8192 : 8192 + 4096);
          tma2d(sb + OFF_PK + i * 8192, &p.xr, (RT_ORD >> i * 4 & 3) * 256, cta * 16, sb + BAR_RT + i * 8);
          if (i == 0) { bulk_load(sb + OFF_KVB, w_r, 2048, sb + BAR_RT); bulk_load(sb + OFF_KVB + 2048, gate_w, 2048, sb + BAR_RT); }
        }
        const uint32_t c = g - MOD_START;
        if (c == MOD_BUFS) mbar_wait(sb + BAR_RTD, 0);
        if (c < MOD_BUFS0 && mu < MOD_CTAS && elect()) {
          PROF_P(true, 192 + c);
          const uint32_t mfull = sb + BAR_MFULL + c * 8, mdst = sb + OFF_MOD + c * 8192;
          mbar_expect_tx(mfull, c ? 8192 : 8192 + 2048);
          tma3d(mdst, &p.gate, mu * 32, c * 16, 0, mfull); tma3d(mdst + 4096, &p.up, mu * 32, c * 16, 0, mfull);
        }
        const uint32_t pc = g - PF_MOD;
        if (pc < 16 && elect()) bulk_prefetch((cta & 64 ? w_up : w_gate) + (size_t)(pc * 64 + (cta & 63)) * F_, F_ * 2);
        full += 8; dst += STAGE_BYTES; c1 += 64;
        if ((g & 3) == 3) { full -= 32; dst -= 4 * STAGE_BYTES; }
        if (g == 15) { c0 += 512; c1 = 768; }
        if (g == 19) c1 = 0;
      }
      mbar_arrive_warp(sb + BAR_W31);
      const uint32_t lowb = (1u << (tn & 6) * 4) - 1;
      uint64_t slabs = (uint64_t)((0xFEDCBA98u & lowb) | (0xFEDCBAu & ~lowb)) << 40 | (uint64_t)(8 + (tn ^ 1)) << 36 | (uint64_t)(8 + tn) << OWN * 4 |
                       (0x76543210ull & ~(~0ull << OWN * 4)) | (0x765432100ull & ~0ull << (OWN * 4 + 4));
      uint32_t ph = 1;
      c1 = 0;
#pragma unroll 1
      for (int g = 0; g < 16; g++) {
        mbar_wait(full + (BAR_EMPTY - BAR_FULL), ph);
        if (elect()) tma3d(dst, &p.wo, 0, c1, tn * 2, full);
        if (elect()) mbar_expect_tx(full, BO_BYTES);
        PROF_P(lane == 0, 96 + g);
        if (g == OWN && elect()) mbar_arrive(full);
        full += 8; dst += O_BYTES; slabs >>= 4; c1 = ((uint32_t)slabs & 15) * 64;
        if (full == sb + BAR_EMPTY) { full -= 40; dst -= 5 * O_BYTES; ph ^= 1; }
      }
    } else if (warp == 14) {
      if (mu < MOD_CTAS) {
        uint32_t full = sb + BAR_MFULL, dst = sb + OFF_MOD, ph = 0;
#pragma unroll 1
        for (int c = MOD_BUFS0; c < 24; c++) {
          mbar_wait(full + (BAR_MEMPTY - BAR_MFULL), ph);
          PROF_P(lane == 0, 192 + c);
          if (c < 16) {
            if (elect()) { tma3d(dst, &p.gate, mu * 32, c * 16, 0, full); tma3d(dst + 4096, &p.up, mu * 32, c * 16, 0, full); }
          } else if (elect()) tma3d(dst, &p.down, 0, mu * 32 + (c - 16) * 4, 0, full);
          if (elect()) mbar_expect_tx(full, 8192);
          full += 8; dst += 8192;
          if (dst == sb + OFF_PK) { full -= MOD_BUFS * 8; dst = sb + OFF_MOD; ph ^= 1; }
        }
      }
      if (elect()) {
      mbar_wait(sb + BAR_IDX, 0);
      const bool paired = lds32(sb + OFF_MISC + 28) < 0x200;
      const uint32_t pb = peer_addr(sb);
      mbar_wait(sb + BAR_EMPTY + PEER % 5 * 8, 0);
      mbar_expect_tx(sb + BAR_FULL + PEER % 5 * 8, A_BYTES);
      if (paired) mbar_arrive_peer(pb + BAR_PA);
      mbar_wait(sb + BAR_OST, 0);
      mbar_expect_tx(sb + BAR_X, 32768);
      tma2d(sb + OFF_PK, &p.x, tn * 128, tm * 128, sb + BAR_X);
      tma2d(sb + OFF_V, &p.x, tn * 128 + 64, tm * 128, sb + BAR_X);
      if (paired) {
        mbar_wait(sb + BAR_PA, 0);
        mbar_wait(sb + BAR_OWN, 0);
        bulk_push(pb + OFF_RING + PEER % 5 * O_BYTES, sb + OFF_MOD, A_BYTES, pb + BAR_FULL + PEER % 5 * 8);
        mbar_wait(sb + BAR_EMPTY + PEER % 5 * 8, 1);
        mbar_arrive_peer(pb + BAR_PA);
        mbar_wait(sb + BAR_PA, 1);
      } else {
        mbar_wait(sb + BAR_EMPTY + OWN % 5 * 8, 1);
        bulk_load(sb + OFF_RING + PEER % 5 * O_BYTES, gs->o[tm][8 + (tn ^ 1)], A_BYTES, sb + BAR_FULL + PEER % 5 * 8);
      }
      }
    } else if (elect()) {
#pragma unroll 1
      for (int i = 2; i < 8; i++) asm volatile("prefetch.tensormap [%0];" ::"l"(&p.x + i) : "memory");
      mbar_wait_bounded(sb + BAR_DONE, 0);
    }
  } else if (wg == 2) {
    asm volatile("setmaxnreg.dec.sync.aligned.u32 40;");
    const int mw = warp & 3;
    if (mw == 0) {
      const unsigned tag = (ld_relaxed(&gs->rslot[tn][cta]) + 1) & 0xFFF;
#pragma unroll
      for (int i = 0; i < 4; i++)
        if (lane < NCLR) ((float4*)gs)[cta * (NCLR * 4) + i * NCLR + lane] = make_float4(0.f, 0.f, 0.f, 0.f);
      if (lane == 29) st_relaxed(&gs->block[cta], blockIdx.x << 12 | tag);
      fence_release();
      nb_sync(NB_KEY, 160);
      const uint4 k4 = lds128(sb + OFF_MISC);
      if (lane < 8) st_relaxed(&gs->rslot[lane][cta], max(max(k4.x, k4.y), max(k4.z, k4.w)) | tag);
      if (lane < 16) st_relaxed(&gs->gslot[cta * 16 + lane], lds32(sb + OFF_G + lane * 4) | tag);
      PROF(lane == 0, 20);
      uint4 r4;
      do {
        __nanosleep(RT_SLEEP);
        r4 = ld_relaxed4(&gs->rslot[tn][lane * 4]);
      } while (!__all_sync(~0u, (((r4.x ^ tag) | (r4.y ^ tag) | (r4.z ^ tag) | (r4.w ^ tag)) & 0xFFF) == 0));
      const int c0 = 0xFFF0 - lane * 64;
      unsigned key = max(max((r4.x & 0xFFFF0000u) | (c0 + ((r4.x >> 12) & 15)), (r4.y & 0xFFFF0000u) | (c0 - 16 + ((r4.y >> 12) & 15))),
                         max((r4.z & 0xFFFF0000u) | (c0 - 32 + ((r4.z >> 12) & 15)), (r4.w & 0xFFFF0000u) | (c0 - 48 + ((r4.w >> 12) & 15))));
      key = __reduce_max_sync(~0u, key);
      if (elect()) {
        sts32(sb + OFF_MISC + 16, key);
        sts32(sb + OFF_MISC + 24, tag & 1);
        if (mu < MOD_CTAS) bulk_load(sb + OFF_XSEL, px + (size_t)(0xFFFF - (key & 0xFFFF)) * D_, 2048, sb + BAR_MFULL);
      }
      PROF(lane == 0, 21);
      unsigned nb;
      do {
        r4 = ld_relaxed4(&gs->gslot[tm * 128 + lane * 4]);
        nb = ld_relaxed(&gs->block[cta ^ 1]);
      } while (!__all_sync(~0u, (((r4.x ^ tag) | (r4.y ^ tag) | (r4.z ^ tag) | (r4.w ^ tag) | (nb ^ tag)) & 0xFFF) == 0));
      sts128(sb + OFF_G + lane * 16, r4.x & 0xFFFF0000u, r4.y & 0xFFFF0000u, r4.z & 0xFFFF0000u, r4.w & 0xFFFF0000u);
      sts32(sb + OFF_MISC + 28, (PAIRED && nb >> 12 == (blockIdx.x ^ 1) ? 0x1FF : 0x3FF) & ~((1 << PC) - 1 | 1 << OWN));
      fence_acquire();
      __syncwarp();
      mbar_arrive_warp(sb + BAR_IDX);
    }
    PROF(tid == 256, 22);
    if (mu >= MOD_CTAS) {
      mbar_arrive_warp(sb + BAR_IDX);
      mbar_arrive_warp(sb + BAR_OA);
    } else {
      const uint32_t wp = sb + OFF_MOD + (mw >> 1) * 4096 + (mw & 1) * 512 + lane * 16;
      uint32_t mp = sb + OFF_XSEL - 128 + (mw & 1) * 64 + (lane >> 2) * 8, mc = 128;
      float acc[8] = {0.f, 0.f, 0.f, 0.f, 0.f, 0.f, 0.f, 0.f};
      uint32_t b = ~0u, ph = 0, a = sb + OFF_ONES - 3072;
      float m3 = 0.f;
      const uint32_t zero = lds32(sb + OFF_ONES) & 1;
      uint2 m = make_uint2(0, 0);
      uint4 w0 = make_uint4(0, 0, 0, 0), w1 = w0, w2 = w0, w3 = w0;
#pragma unroll 1
      for (int c = -1;; c++) {
        fma8(acc, w3, m3);
        w3 = lds128(a + 3072);
        const uint32_t rel = sb + BAR_MEMPTY + b * 8;
        if (c == 16) {
          const uint32_t ft = fresh_tid(), fl = ft & 31;
          sts32(sb + OFF_PART + (ft & 96) * 4 + ((ft & 3) * 8 + (fl >> 2)) * 4, __float_as_uint(butterfly8(acc, fl, 4)));
          nb_sync(NB_MODW, 128);
          const float* part = (const float*)(smem + OFF_PART) + fl;
          const float gp = bf_round(part[0] + part[32]), up = bf_round(part[64] + part[96]);
          *(__nv_bfloat16*)(smem + OFF_PART + 512 + fl * 2) = __float2bfloat16_rn(bf_round(gp * sigmoidf_(gp)) * up);
          __syncwarp();
          mp = sb + OFF_PART + 512; mc = 8;
          m = lds64(mp);
#pragma unroll
          for (int i = 0; i < 8; i++) acc[i] = 0.f;
          PROF(lane == 0 && mw == 0, 23);
        }
        if (++b == (c < MOD_BUFS0 ? MOD_BUFS0 : MOD_BUFS)) { b = 0; ph ^= 1; }
        const uint32_t ok = mbar_test(sb + BAR_MFULL + b * 8, ph);
        fma8(acc, w0, bf_lo(m.x));
        if (c >= 0) mbar_arrive_warp(rel + ((w3.x | __float_as_uint(acc[7])) & zero));
        fma8(acc, w1, bf_hi(m.x));
        fma8(acc, w2, bf_lo(m.y));
        m3 = bf_hi(m.y);
        if (c == 23) break;
        if (!ok) mbar_wait(sb + BAR_MFULL + b * 8, ph);
        a = wp + b * 8192;
        mp += mc;
        m = lds64(mp);
        w0 = lds128(a); w1 = lds128(a + 1024); w2 = lds128(a + 2048);
      }
      fma8(acc, w3, m3);
      mbar_arrive_warp(sb + BAR_OA);
      float* yacc = gs->y[tn] + (fresh_tid() & 127) * 8;
      red_add4(yacc, acc[0], acc[1], acc[2], acc[3]);
      red_add4(yacc + 4, acc[4], acc[5], acc[6], acc[7]);
      PROF(lane == 0 && mw == 0, 25);
      nb_sync(NB_MODW, 128);
      if (mw == 0 && elect()) { fence_release(); red_add(gs->cnt[32], 1); }
      PROF(lane == 0 && mw == 0, 24);
    }
    const unsigned key = lds32(sb + OFF_MISC + 16);
    const int sel = 0xFFFF - (int)(key & 0xFFFF) - tm * 128;
    if (mw == 0 && sel >= 0 && sel < 128) {
      if (elect()) wait_counter(gs->cnt[32], MOD_CTAS);
      __syncwarp();
      const unsigned k16 = key >> 16;
      const float rs = bf_round(sigmoidf_(__uint_as_float(((k16 & 0x8000u) ? (k16 & 0x7FFFu) : (~k16 & 0xFFFFu)) << 16)));
      float4 v = make_float4(0.f, 0.f, 0.f, 0.f);
#pragma unroll 4
      for (int i = 0; i < 8; i++) {
        const float4 u = ld_relaxed_f4(gs->y[i] + tn * 128 + lane * 4);
        v.x += u.x; v.y += u.y; v.z += u.z; v.w += u.w;
      }
      mbar_wait(sb + BAR_X, 0);
      uint2* xp = (uint2*)(smem + OFF_PK + (lane >> 4) * 16384 + sel * 128 + ((((lane >> 1) & 7) ^ (sel & 7)) << 4) + (lane & 1) * 8);
      const uint2 xv = *xp;
      *xp = make_uint2(pack2(bf_lo(xv.x) + bf_round(bf_round(v.x) * rs), bf_hi(xv.x) + bf_round(bf_round(v.y) * rs)),
                       pack2(bf_lo(xv.y) + bf_round(bf_round(v.z) * rs), bf_hi(xv.y) + bf_round(bf_round(v.w) * rs)));
      __syncwarp();
      mbar_arrive_warp(sb + BAR_Y);
    }
  } else {
    asm volatile("setmaxnreg.inc.sync.aligned.u32 224;");
    const int w = warp & 3, wt = tid & 127;
    const int nb_self = NB_WG0 + wg;
    const uint32_t da0 = mkdesc(sb + OFF_RING, 16), db0 = mkdesc(sb + OFF_RING + A_BYTES, 8192);

    if (wg == 1) {
      float s[8] = {0.f, 0.f, 0.f, 0.f, 0.f, 0.f, 0.f, 0.f};
      const uint32_t zero = lds32(sb + OFF_ONES) & 1;
      uint32_t mask = 0xffff0000u;
#pragma unroll 1
      for (int i = 0; i < 4; i++) {
        const uint32_t u = RT_ORD >> i * 4 & 3;
        mbar_wait(sb + BAR_RT + i * 8, 0);
        const uint4 wr = lds128(sb + OFF_KVB + u * 512 + lane * 16), gw = lds128(sb + OFF_KVB + 2048 + u * 512 + lane * 16);
        uint4 xv[4];
#pragma unroll
        for (int r = 0; r < 4; r++) xv[r] = lds128(sb + OFF_PK + i * 8192 + (w * 4 + r) * 512 + lane * 16);
        const float wf[16] = {bf_lo(wr.x), bf_hi(wr.x), bf_lo(wr.y), bf_hi(wr.y), bf_lo(wr.z), bf_hi(wr.z), bf_lo(wr.w), bf_hi(wr.w),
                              bf_lo(gw.x), bf_hi(gw.x), bf_lo(gw.y), bf_hi(gw.y), bf_lo(gw.z), bf_hi(gw.z), bf_lo(gw.w), bf_hi(gw.w)};
#pragma unroll
        for (int r = 0; r < 4; r++) {
          const uint4 xq = xv[r];
          const float xf[8] = {bf_lo(xq.x), __uint_as_float(xq.x & mask), bf_lo(xq.y), bf_hi(xq.y), bf_lo(xq.z), bf_hi(xq.z), bf_lo(xq.w), bf_hi(xq.w)};
#pragma unroll
          for (int j = 0; j < 8; j++) { s[2 * r] = fmaf(xf[j ^ 1], wf[j ^ 1], s[2 * r]); s[2 * r + 1] = fmaf(xf[j ^ 1], wf[8 + (j ^ 1)], s[2 * r + 1]); }
          mask = ((__float_as_uint(s[2 * r]) | __float_as_uint(s[2 * r + 1])) & zero) | 0xffff0000u;
        }
      }
      mbar_arrive_warp(sb + BAR_RTD);
      float v = butterfly8(s, lane, 1);
      PROF_C(wt == 0 && v != 12345.f, 19);
      v += __shfl_xor_sync(~0u, v, 8);
      v = bf_round(v + __shfl_xor_sync(~0u, v, 16));
      const unsigned rb = __float_as_uint(v) >> 16, row = w * 4 + ((lane & 7) >> 1);
      unsigned key = (lane & 1) ? 0u : ((((rb & 0x8000u) ? (~rb & 0xFFFFu) : (rb | 0x8000u)) << 16) | ((15 - row) << 12));
      key = __reduce_max_sync(~0u, key);
      if (lane == 0) sts32(sb + OFF_MISC + w * 4, key);
      if (lane < 8 && (lane & 1)) sts32(sb + OFF_G + row * 4, __float_as_uint(bf_round(sigmoidf_(v))));
      nb_arrive(NB_KEY, 160);
      nb_sync(NB_ORDER_AB, 256);
    }

    uint32_t pq[2][4][4];
    float4* const kvacc = &gs->kv[wg][tn][0][wt];
    {
      float acc[2][96];
      PROF_C(wt == 0, 1 + wg * 8);
#pragma unroll 1
      for (int g = 0; g < 14; g++) {
        const uint32_t s = g & 3;
        const uint32_t da = da0 + s * (STAGE_BYTES >> 4), db = db0 + s * (STAGE_BYTES >> 4);
        mbar_wait(sb + BAR_FULL + s * 8, (g >> 2) & 1);
        PROF_C(wt == 0, 64 + wg * 16 + g);
#pragma unroll
        for (int m = 0; m < 2; m++) {
          wg_fence();
#pragma unroll
          for (int kk = 0; kk < 4; kk++) mma_qkv(acc[m], da + (m * 512 + kk * 2), db + kk * 128, kk ? 1 : g);
          wg_commit();
          if (m == 0) {
            wg_wait<1>();
            if (g) mbar_arrive_warp(sb + BAR_EMPTY + ((g + 3) & 3) * 8);
          }
        }
      }
      auto half_step = [&](int m, int g) {
        wg_fence();
#pragma unroll
        for (int kk = 0; kk < 4; kk++)
          mma_qkv(acc[m], da0 + ((g & 3) * (STAGE_BYTES >> 4) + m * 512 + kk * 2), db0 + ((g & 3) * (STAGE_BYTES >> 4) + kk * 128), 1);
        wg_commit();
      };
#pragma unroll
      for (int g = 14; g < 16; g++) {
        mbar_wait(sb + BAR_FULL + (g & 3) * 8, 1);
        PROF_C(wt == 0, 64 + wg * 16 + g);
        half_step(0, g);
        if (g == 14) { wg_wait<1>(); mbar_arrive_warp(sb + BAR_EMPTY + ((g + 3) & 3) * 8); }
      }
      half_step(1, 14);
      half_step(1, 15);
      if (wg == 0) nb_arrive(NB_ORDER_AB, 256);
      mbar_wait(sb + BAR_IDX, 0);
      if (wg == 1) nb_sync(NB_STG, 256);
      wg_wait<2>();
      PROF_C(wt == 0, 3 + wg * 8);

      const uint32_t st_row = (uint32_t)(w * 16 + (lane & 15)) * 128;
      float c[36];
      const uint32_t dk = mkdesc(sb + OFF_PK, 16), dv = mkdesc(sb + OFF_V, OFF_ONES - OFF_V);
      uint32_t l2k[8 + PA];
#pragma unroll
      for (int u = 0; u < PA; u++) l2k[u] = 0x3FB8AA3Bu;
#pragma unroll
      for (int u = 0; u < 8; u++) {
        const int m = u >> 2, j = u & 3;
        const uint32_t a = sb + m * 8192 + st_row + ((((lane >> 4) + 2 * j) ^ (lane & 7)) << 4);
        const float* k = &acc[m][32 + 8 * j];
        const float l = __uint_as_float(l2k[u]);
        if (u == M1) {
          wg_wait<1>();
          mbar_arrive_warp(sb + BAR_EMPTY + 2 * 8);
        }
        if (u == MM) {
          wg_wait<0>();
          mbar_arrive_warp(sb + BAR_EMPTY + 3 * 8);
        }
        const float* v = &acc[m][64 + 8 * j];
        stsm4(a + OFF_V, pack2(v[0], v[1]), pack2(v[2], v[3]), pack2(v[4], v[5]), pack2(v[6], v[7]));
        const uint32_t r0 = phi2(k[0], k[1], l), r1 = phi2(k[2], k[3], l), r2 = phi2(k[4], k[5], l), r3 = phi2(k[6], k[7], l);
        stsm4(a + OFF_PK, r0, r1, r2, r3);
        if (u + PA < 8) l2k[u + PA] = lds32(sb + OFF_MISC + 20);
      }
      fence_async_smem();
      nb_sync(nb_self, 128);
      PROF_C(wt == 0, 8 + wg * 8);
      wg_fence();
#pragma unroll
      for (int kk = 0; kk < 8; kk++) mma_ktv(c, dk + kk * 128, dv + (kk * 128 - (kk << 23)), kk ? 1 : 0);
      wg_commit();
      if (wg == 1) nb_arrive(NB_ORDER_BO, 256);
      auto reduce = [&](float4* dst, int gap) {
        wg_wait<0>();
        PROF_C(wt == 0, 4 + wg * 8);
        float u[18];
#pragma unroll
        for (int i = 0; i < 16; i++) u[i] = w >= 2 ? c[16 + i] : c[i];
        u[16] = __shfl_down_sync(~0u, u[15], 1);
        u[17] = lane & 2 ? c[34] : c[32];
#pragma unroll
        for (int i = 0; i < 5; i++) {
          if (gap && i) __nanosleep(gap);
          red_add4(dst + i * 128, u[3 * i], u[3 * i + 1], u[3 * i + 2], i < 3 && !(lane & 1) ? u[i == 0 ? 15 : i == 1 ? 17 : 16] : 1.f);
        }
      };
      const uint32_t zero = lds32(sb + OFF_ONES) & 1;
      if (wg) reduce(kvacc, 0);
      const float l2e = __uint_as_float(lds32(sb + OFF_MISC + 20));
      uint32_t dep = 0;
#pragma unroll
      for (int u = 0; u < 8; u++) {
#pragma unroll
        for (int i = 0; i < 4; i++) dep |= pq[u >> 2][u & 3][i] = phi2(acc[u >> 2][8 * (u & 3) + 2 * i], acc[u >> 2][8 * (u & 3) + 2 * i + 1], l2e);
      }
      float4* const kvp = kvacc + (dep & zero);
      if (!wg) reduce(kvp, RED_SLEEP);
      PROF_C(wt == 0 && kvp == kvacc, 34 + wg * 2);
      for (int tries = wg ? 0 : 9;; tries++) {
        if (tries > RETRY)
          while (ld_relaxed((const unsigned*)&(kvp - lane)[NV * 128 - 128 + 31].w) != 0x41800000u) __nanosleep(wg ? KV_SLEEP : KV_SLEEP_A);
        float4 kv[NV];
#pragma unroll
        for (int i = 0; i < NV; i++) kv[i] = ld_relaxed_f4(kvp + i * 128);
        const uint32_t kb = sb + OFF_KVB + (w >> 1) * 2560 + (w & 1) * 256;
        const uint32_t ka = kb + (lane >> 4) * 512 + (lane & 15) * 16;
        stsm4(ka, pack2(kv[0].x, kv[0].y), pack2(kv[0].z, kv[1].x), pack2(kv[1].y, kv[1].z), pack2(kv[2].x, kv[2].y));
        const uint32_t zz = pack2(kv[1].w, kv[1].w);
        if (!(lane & 1)) sts128(kb + 2048 + (lane & 2) * 64 + (lane >> 2) * 16, zz, zz, zz, zz);
        const float u15 = __shfl_up_sync(~0u, kv[2].w, 1);
        stsm4(ka + 1024, pack2(kv[2].z, kv[3].x), pack2(kv[3].y, kv[3].z), pack2(kv[4].x, kv[4].y), pack2(kv[4].z, lane & 1 ? u15 : kv[0].w));
        const bool ok = !(lane & 1) || kv[0].w + kv[1].w + kv[2].w + kv[3].w + kv[4].w == 80.f;
        if (__all_sync(~0u, ok)) { PROF_V(wg && lane == 0, 40 + w, tries * 100 + 2); break; }
      }
    }
    {
      PROF_C(wt == 0, 5 + wg * 8);
      fence_async_smem();
      nb_sync(nb_self, 128);
      float o[2][2][20];
      const uint32_t dz = mkdesc(sb + OFF_KVB, 128);
      wg_fence();
#pragma unroll
      for (int m = 0; m < 2; m++) {
#pragma unroll
        for (int h = 0; h < 2; h++)
#pragma unroll
          for (int kk = 0; kk < 2; kk++) mma_qkvz(o[m][h], pq[m][2 * h + kk], dz + (h * 160 + kk * 16), kk);
        wg_commit();
      }
      const uint32_t tmask = (lane & 3) == (lane >> 3), tbit = lds32(sb + OFF_MISC + 24) & tmask;
      float gr[2][2], sc[4];
#pragma unroll
      for (int i = 0; i < 4; i++) gr[i >> 1][i & 1] = __uint_as_float(lds32(sb + OFF_G + ((i >> 1) * 64 + (i & 1) * 8 + w * 16 + (lane >> 2)) * 4));
      if (wg == 1) {
        mbar_arrive_warp(sb + BAR_OST);
        mbar_wait(sb + BAR_OA, 0);
      }
      const uint32_t os = sb + (wg ? OFF_MOD : OFF_PK) + w * 2048;
      uint8_t* const og = (uint8_t*)gs->o[tm][wg * 8 + tn] + w * 2048;
#pragma unroll
      for (int m = 0; m < 2; m++) {
        if (m == 0) wg_wait<1>();
        if (m == 0) PROF_C(wt == 0, 6 + wg * 8);
#pragma unroll
        for (int h = 0; h < 2; h++) {
          const float* oo = o[m][h];
          uint32_t pin = 0;
          if (!m && h) {
            wg_wait<0>();
#pragma unroll
            for (int i = 0; i < 4; i++) pin |= __float_as_uint(sc[i] = gr[1][i & 1] * rcp(o[1][i >> 1][16 + (i & 1) * 2] + 1e-6f));
            pin &= __float_as_uint(gr[0][0]) & 16;
          }
          const float s0 = m ? sc[2 * h] : gr[m][0] * rcp(oo[16] + 1e-6f), s1 = m ? sc[2 * h + 1] : gr[m][1] * rcp(oo[18] + 1e-6f);
#pragma unroll
          for (int j = 0; j < 2; j++)
            stsm4(os + m * 8192 + (lane & 15) * 128 + ((((lane >> 4) + 4 * h + 2 * j) ^ (lane & 7)) << 4) + (j ? pin : 0),
                  (pack2(oo[8 * j] * s0, oo[8 * j + 1] * s0) & ~tmask) | tbit, (pack2(oo[8 * j + 2] * s1, oo[8 * j + 3] * s1) & ~tmask) | tbit,
                  pack2(oo[8 * j + 4] * s0, oo[8 * j + 5] * s0), pack2(oo[8 * j + 6] * s1, oo[8 * j + 7] * s1));
        }
        fence_async_smem();
        __syncwarp();
        if (elect()) bulk_store(og + m * 8192, os + m * 8192, 2048);
      }
      if (elect()) {
        bulk_commit();
        if (wg) mbar_arrive(sb + BAR_OWN);
        PROF(wt == 0, 7 + wg * 8);
        if (!wg) red_add(gs->cnt[tm], 1u << tn * 4);
        asm volatile("cp.async.bulk.wait_group.read 0;" ::: "memory");
        PROF(wt == 0, 17 + wg);
        PROF(wt == 96, 38 + wg);
      }
    }

    __syncwarp();
    const uint32_t par = lds32(sb + OFF_MISC + 24), cw = lane * 32 + (lane & 4) * 4 + (lane >> 3) * 4;
    auto check_tile = [&](int g, uint32_t s) {
      const uint32_t a = sb + OFF_RING + s * O_BYTES + w * 2048, fix = sb + BAR_FIX + warp * 8;
      for (;;) {
        const uint32_t u0 = lds32(a + cw), u1 = lds32(a + cw + 1024), u2 = lds32(a + cw + 8192), u3 = lds32(a + cw + 9216);
        if (__all_sync(~0u, !(mism(mism(u0, u1, par), mism(u2, u3, par), 0) & 1))) break;
        PROF_V(lane == 0, 44 + g, 102);
        const int slab = g < OWN ? g : g < PEER ? g - 1 : g == PEER ? 8 + (tn ^ 1) : g - 10 < (tn & 6) ? g - 2 : g;
        const uint4* src = gs->o[tm][slab] + w * 128;
        const uint32_t ph = !mbar_test(fix, 1);
        fence_async_smem();
        __syncwarp();
        if (elect()) { mbar_expect_tx(fix, 4096); bulk_load(a, src, 2048, fix); bulk_load(a + 8192, src + 512, 2048, fix); }
        mbar_wait(fix, ph);
      }
    };
    if (wg == 1) {
#pragma unroll 1
      for (int g = 10; g < 16; g++) {
        const uint32_t s = g == 15 ? 0 : g - 10;
        mbar_wait(sb + BAR_LAND + (g - 10) * 8, 0);
        PROF_C(wt == 0, 214 + g);
        check_tile(g, s);
        if (w) nb_arrive(NB_CHK + (g & 1), 128);
        else { nb_sync(NB_CHK + (g & 1), 128); mbar_arrive_warp(sb + BAR_FULL + s * 8); }
        if (g & 1) nb_sync(nb_self, 128);
      }
    } else {
      nb_arrive(NB_STG, 256);
      float acc[2][64];
      mbar_wait(sb + BAR_W31, 0);
#pragma unroll 1
      for (int g = 0; g < PC; g++) { mbar_wait(sb + BAR_EMPTY + g * 8, 1); mbar_wait(sb + BAR_FULL + g * 8, 0); check_tile(g, g); }
      const uint32_t chk = __shfl_sync(~0u, lds32(sb + OFF_MISC + 28), 0);
      nb_sync(NB_ORDER_BO, 256);
      PROF_C(wt == 0, 26);
      uint32_t xr[2][8][4], q[2][2];
      const uint32_t ta = sb + OFF_PK + (uint32_t)(w * 16 + (lane & 15)) * 128;
#pragma unroll 1
      for (int g = 0; g < 13 - TL; g++) {
        const uint32_t r = g * 52 >> 8, s = g - r * 5;
        const uint32_t da = da0 + (g == OWN ? 5 : s) * (O_BYTES >> 4), db = db0 + s * (O_BYTES >> 4);
        if (g == OWN) {
          wg_wait<0>();
          mbar_arrive_warp(sb + BAR_EMPTY + (OWN + 4) % 5 * 8);
          mbar_wait(sb + BAR_OWN, 0);
        }
        mbar_wait(sb + BAR_FULL + s * 8, r & 1);
        if (chk >> g & 1) check_tile(g, s);
        PROF_C(wt == 0, 96 + g);
        wg_fence();
#pragma unroll
        for (int kk = 0; kk < 4; kk++)
#pragma unroll
          for (int m = 0; m < 2; m++) mma_out(acc[m], da + (m * 512 + kk * 2), db + kk * 128, kk ? 1 : g);
        wg_commit();
        wg_wait<1>();
        if (~(1 | 1 << OWN) >> g & 1) mbar_arrive_warp(sb + BAR_EMPTY + (s ? s - 1 : 4) * 8);
      }
      mbar_wait(sb + BAR_X, 0);
      if (((0xFFFF - (lds32(sb + OFF_MISC + 16) & 0xFFFF)) >> 7) == tm) mbar_wait(sb + BAR_Y, 0);
#pragma unroll
      for (int u = 0; u < 4; u++) {
        const int m = u >> 1, g = 13 - TL + u;
        const float g1 = 1.f - __uint_as_float(lds32(sb + OFF_G + (m * 64 + w * 16 + (u & 1) * 8 + (lane >> 2)) * 4));
        q[m][u & 1] = pack2(g1, g1);
#pragma unroll
        for (int j = 0; j < 4; j++) ldsm4(ta + (u & 1) * 16384 + m * 8192 + ((((lane >> 4) + 2 * j) ^ (lane & 7)) << 4), xr[m][(u & 1) * 4 + j]);
        if (u == 3) break;
        mbar_wait(sb + BAR_FULL + g % 5 * 8, g / 5 & 1);
        PROF_C(wt == 0, 96 + g);
        wg_fence();
#pragma unroll
        for (int kk = 0; kk < 4; kk++)
#pragma unroll
          for (int mm = 0; mm < 2; mm++)
            mma_out(acc[mm], da0 + (g % 5 * (O_BYTES >> 4) + mm * 512 + kk * 2), db0 + (g % 5 * (O_BYTES >> 4) + kk * 128), 1);
        wg_commit();
        wg_wait<1>();
        if (g <= 11) mbar_arrive_warp(sb + BAR_EMPTY + (g + 4) % 5 * 8);
      }
      auto half_step = [&](int m, int g) {
        if (m == 0) { mbar_wait(sb + BAR_FULL + g % 5 * 8, g / 5 & 1); PROF_C(wt == 0, 96 + g); wg_fence(); }
#pragma unroll
        for (int kk = 0; kk < 4; kk++)
          mma_out(acc[m], da0 + (g % 5 * (O_BYTES >> 4) + m * 512 + kk * 2), db0 + (g % 5 * (O_BYTES >> 4) + kk * 128), 1);
      };
      auto stage = [&](int m, int j0, int j1) {
#pragma unroll
        for (int j = j0; j < j1; j++) {
          const float* v = &acc[m][8 * j];
          stsm4(ta + (j >> 2) * 16384 + m * 8192 + ((((lane >> 4) + 2 * (j & 3)) ^ (lane & 7)) << 4),
                fma_bf2(xr[m][j][0], q[m][0], pack2(v[0], v[1])), fma_bf2(xr[m][j][1], q[m][1], pack2(v[2], v[3])),
                fma_bf2(xr[m][j][2], q[m][0], pack2(v[4], v[5])), fma_bf2(xr[m][j][3], q[m][1], pack2(v[6], v[7])));
        }
      };
      auto leave_tma = [&](int m, int h) {
        fence_async_smem();
        __syncwarp();
        if (elect()) tma2d_store(&p.out, sb + OFF_PK + h * 16384 + m * 8192 + w * 2048, tn * 128 + h * 64, tm * 128 + m * 64 + w * 16);
      };
      auto leave = [&](int m, int h) {
        __syncwarp();
        const uint32_t r = lane >> 3;
        uint4 v[4];
#pragma unroll
        for (int i = 0; i < 4; i++) v[i] = lds128(sb + OFF_PK + h * 16384 + m * 8192 + w * 2048 + (r + 4 * i) * 128 + (((lane ^ (r + 4 * i)) & 7) << 4));
        char* const dst = (char*)pout + (size_t)(tm * 128 + m * 64 + w * 16 + r) * (D_ * 2) + tn * 256 + h * 128 + (lane & 7) * 16;
#pragma unroll
        for (int i = 0; i < 4; i++) asm volatile("st.global.v4.u32 [%0], {%1, %2, %3, %4};" ::"l"(dst + i * 4 * D_ * 2), "r"(v[i].x), "r"(v[i].y), "r"(v[i].z), "r"(v[i].w) : "memory");
      };
#pragma unroll
      for (int g = 16 - TL; g < 16; g++) half_step(0, g);
      wg_commit();
#pragma unroll
      for (int g = 16 - TL; g < 16; g++) half_step(1, g);
      wg_commit();
      mbar_arrive_warp(sb + BAR_DONE);
      wg_wait<1>();
      PROF(wt == 0, 35);
      stage(0, 0, 4);
      leave_tma(0, 0);
      stage(0, 4, 8);
      leave_tma(0, 1);
      if (elect()) bulk_commit();
      PROF(wt == 0, 33);
      wg_wait<0>();
      PROF(wt == 0, 31);
#pragma unroll
      for (int h = 0; h < 2; h++) { stage(1, 4 * h, 4 * h + 4); leave(1, h); }
      if (elect()) asm volatile("cp.async.bulk.wait_group.read 0;" ::: "memory");
      PROF(wt == 0, 32);
    }
  }
}

typedef CUresult (*EncodeFn)(CUtensorMap*, CUtensorMapDataType, cuuint32_t, void*, const cuuint64_t*, const cuuint64_t*, const cuuint32_t*,
                             const cuuint32_t*, CUtensorMapInterleave, CUtensorMapSwizzle, CUtensorMapL2promotion, CUtensorMapFloatOOBfill);

void encode(EncodeFn fn, CUtensorMap* m, const void* ptr, int rank, const cuuint64_t* dims, const cuuint64_t* strides, const cuuint32_t* box,
            CUtensorMapSwizzle sw, CUtensorMapDataType dt = CU_TENSOR_MAP_DATA_TYPE_BFLOAT16) {
  const cuuint32_t es[3] = {1, 1, 1};
  fn(m, dt, rank, const_cast<void*>(ptr), dims, strides, box, es, CU_TENSOR_MAP_INTERLEAVE_NONE, sw,
     CU_TENSOR_MAP_L2_PROMOTION_L2_128B, CU_TENSOR_MAP_FLOAT_OOB_FILL_NONE);
}

}

extern "C" void kernel_launch(void* const* d_in, const int* in_sizes, int n_in, void* d_out, int out_size) {
  (void)in_sizes; (void)n_in; (void)out_size;
  EncodeFn fn = nullptr;
  cudaDriverEntryPointQueryResult qr;
  cudaGetDriverEntryPoint("cuTensorMapEncodeTiled", (void**)&fn, cudaEnableDefault, &qr);

  Params p;
  {
    const cuuint64_t dims[2] = {D_, S_}, str[1] = {D_ * 2};
    const cuuint32_t box[2] = {64, 128}, box_st[2] = {64, 16}, box_r[2] = {256, 16};
    encode(fn, &p.xr, d_in[0], 2, dims, str, box_r, CU_TENSOR_MAP_SWIZZLE_NONE);
    encode(fn, &p.x, d_in[0], 2, dims, str, box, CU_TENSOR_MAP_SWIZZLE_128B);
    encode(fn, &p.out, d_out, 2, dims, str, box_st, CU_TENSOR_MAP_SWIZZLE_128B);
  }
  {
    const cuuint64_t dims[3] = {D_, D_, 3}, str[2] = {3 * D_ * 2, D_ * 2};
    const cuuint32_t box[3] = {64, 64, 3};
    encode(fn, &p.w, d_in[1], 3, dims, str, box, CU_TENSOR_MAP_SWIZZLE_128B);
  }
  {
    const cuuint64_t dims[3] = {64, D_, D_ / 64}, str[2] = {D_ * 2, 128};
    const cuuint32_t box[3] = {64, 64, 2};
    encode(fn, &p.wo, d_in[2], 3, dims, str, box, CU_TENSOR_MAP_SWIZZLE_128B);
  }
  {
    const cuuint64_t dims[3] = {F_, D_ / 4, 4}, str[2] = {F_ * 8, F_ * 2};
    const cuuint32_t box[3] = {32, 16, 4};
    encode(fn, &p.gate, d_in[5], 3, dims, str, box, CU_TENSOR_MAP_SWIZZLE_NONE);
    encode(fn, &p.up, d_in[6], 3, dims, str, box, CU_TENSOR_MAP_SWIZZLE_NONE);
  }
  {
    const cuuint64_t dims[3] = {D_ / 4, F_, 2}, str[2] = {D_ * 2, D_};
    const cuuint32_t box[3] = {256, 4, 2};
    encode(fn, &p.down, d_in[7], 3, dims, str, box, CU_TENSOR_MAP_SWIZZLE_NONE, CU_TENSOR_MAP_DATA_TYPE_UINT32);
  }
  void* gs = nullptr;
  cudaGetSymbolAddress(&gs, g_scratch);
  typedef const __nv_bfloat16* bp;
  int dev = 0, sms = 0;
  cudaGetDevice(&dev);
  cudaDeviceGetAttribute(&sms, cudaDevAttrMultiProcessorCount, dev);
  const bool by_sm = BYSM && sms == NGRID;
  const auto kernel = by_sm ? fused_kernel<true> : fused_kernel<false>;
  cudaFuncSetAttribute(kernel, cudaFuncAttributeMaxDynamicSharedMemorySize, SMEM_BYTES);
  kernel<<<by_sm ? NGRID : NCTA, NTHREADS, SMEM_BYTES, cudaStreamPerThread>>>((bp)d_in[0], (Scratch*)gs, d_out, (bp)d_in[4], (bp)d_in[8], (bp)d_in[5], p, (bp)d_in[6]);
}
```

```cpp
#include <cuda_runtime.h>
#include <cuda.h>
#include <cuda_bf16.h>
#include <stdint.h>
#include <stddef.h>

namespace {

constexpr int S_ = 2048, D_ = 1024, F_ = 3584;
constexpr int NCTA = 128, NGRID = 132, NTHREADS = 512;
constexpr int MOD_CTAS = F_ / 32;

#define PC 2
#define PRE 2
#define ST1 700
#define RT_G0 2
#define RT_ORD 0x1032
#define RT_SLEEP 500
#define PF_MOD 6
#define MOD_START 9
#define MM 4
#define PA 6
#define RED_SLEEP 32
#define RETRY 1
#define KV_SLEEP_A 128
#define KV_SLEEP 50
#define OWN 5
#define TL 3
#define NOMOD 5
#define FSL 256
#define GMK 0x96
#define M1 1
#define PAIRED 1
#define BYSM 1

constexpr uint32_t A_BYTES = 16384, BQ_BYTES = 24576, BO_BYTES = 16384, STAGE_BYTES = A_BYTES + BQ_BYTES, O_BYTES = A_BYTES + BO_BYTES;
constexpr int MOD_BUFS = 3, MOD_BUFS0 = MOD_BUFS + 1;
static_assert(MOD_START + MOD_BUFS0 <= 16, "first FFN round is requested during wave A");
constexpr uint32_t OFF_RING = 0;
constexpr uint32_t OFF_MOD = 4 * STAGE_BYTES;
constexpr uint32_t OFF_PK = OFF_MOD + MOD_BUFS * 8192;
constexpr uint32_t OFF_V = OFF_PK + 16384;
constexpr uint32_t OFF_ONES = OFF_V + 16384;
constexpr uint32_t OFF_KVB = OFF_ONES + 2048;
constexpr uint32_t OFF_XSEL = OFF_KVB + 5120;
constexpr uint32_t OFF_G = OFF_XSEL + 2048;
constexpr uint32_t OFF_PART = OFF_G + 512;
constexpr uint32_t OFF_MISC = OFF_PART + 576;
constexpr uint32_t OFF_BAR = OFF_MISC + 32;
constexpr uint32_t BAR_FULL = OFF_BAR, BAR_EMPTY = OFF_BAR + 40, BAR_RTD = OFF_BAR + 80, BAR_Y = OFF_BAR + 88, BAR_DONE = OFF_BAR + 96,
                   BAR_X = OFF_BAR + 104, BAR_OA = OFF_BAR + 112, BAR_OWN = OFF_BAR + 120, BAR_OST = OFF_BAR + 128, BAR_PA = OFF_BAR + 136,
                   BAR_W31 = OFF_BAR + 144, BAR_MFULL = OFF_BAR + 152, BAR_MEMPTY = BAR_MFULL + MOD_BUFS0 * 8,
                   BAR_IDX = BAR_MEMPTY + MOD_BUFS * 8;
constexpr uint32_t SMEM_BYTES = OFF_BAR + 384;
static_assert(SMEM_BYTES <= 232448, "smem");

constexpr uint32_t BAR_LAND = OFF_BAR + 256, BAR_FIX = BAR_LAND + 64;
constexpr uint32_t BAR_RT = BAR_FIX;
static_assert(TL == 3 && PRE == 2 && BAR_IDX - OFF_BAR < 256, "warp w initialises barriers 2w and 2w + 1");
constexpr __host__ __device__ uint64_t bar_counts(int first) {
  uint64_t r = 0;
  for (uint32_t i = 0; i < 16; i++) {
    const uint32_t b = OFF_BAR + (first + i) * 8;
    const uint64_t c = b < BAR_EMPTY ? 2 : b == BAR_IDX ? 5 : b == BAR_Y || b == BAR_X || (b >= BAR_PA && b < BAR_MEMPTY) ? 1 : 4;
    r |= c << i * 4;
  }
  return r;
}

constexpr int NB_WG0 = 1, NB_ORDER_AB = 3, NB_ORDER_BO = 4, NB_STG = 5, NB_MODW = 6, NB_KEY = 7, NB_CHK = 8;

constexpr int NV = 5, NCLR = NV * 4 + 5;
struct Scratch {
  float4 kv[2][8][NV][128];
  float y[8][D_];
  unsigned cnt[64][32];
  unsigned gslot[S_];
  unsigned rslot[8][NCTA];
  unsigned spare[128];
  unsigned block[NCTA];
  uint4 o[16][16][1024];
};
static_assert(offsetof(Scratch, gslot) == NCTA * NCLR * 64, "clear size");
__device__ __align__(1024) Scratch g_scratch;

#define PROF(cond, i) do {} while (0)
#define PROF_C(cond, i) do {} while (0)
#define PROF_P(cond, i) do {} while (0)
#define PROF_V(cond, i, v) do {} while (0)

__device__ __forceinline__ void mbar_init(uint32_t bar, int cnt) { asm volatile("mbarrier.init.shared::cta.b64 [%0], %1;" ::"r"(bar), "r"(cnt)); }
__device__ __forceinline__ void mbar_expect_tx(uint32_t bar, uint32_t bytes) { asm volatile("mbarrier.arrive.expect_tx.shared::cta.b64 _, [%0], %1;" ::"r"(bar), "r"(bytes) : "memory"); }
__device__ __forceinline__ void mbar_arrive(uint32_t bar) { asm volatile("mbarrier.arrive.shared::cta.b64 _, [%0];" ::"r"(bar) : "memory"); }
__device__ __forceinline__ uint32_t peer_addr(uint32_t a) {
  uint32_t r;
  asm volatile("{\n.reg .u32 c;\nmov.u32 c, %%cluster_ctarank;\nxor.b32 c, c, 1;\nmapa.shared::cluster.u32 %0, %1, c;\n}" : "=r"(r) : "r"(a));
  return r;
}
__device__ __forceinline__ void mbar_arrive_peer(uint32_t bar) { asm volatile("mbarrier.arrive.shared::cluster.b64 _, [%0];" ::"r"(bar) : "memory"); }
__device__ __forceinline__ uint32_t mism(uint32_t a, uint32_t b, uint32_t p) {
  uint32_t r; asm("lop3.b32 %0, %1, %2, %3, 0x7E;" : "=r"(r) : "r"(a), "r"(b), "r"(p)); return r;
}
__device__ __forceinline__ bool elect() {
  uint32_t r;
  asm volatile("{\n.reg .pred p;\nelect.sync _|p, 0xffffffff;\nselp.u32 %0, 1, 0, p;\n}" : "=r"(r));
  return r;
}
__device__ __forceinline__ uint32_t fresh_tid() { uint32_t r; asm volatile("mov.u32 %0, %%tid.x;" : "=r"(r)); return r; }
__device__ __forceinline__ void mbar_arrive_warp(uint32_t bar) {
  asm volatile("{\n.reg .pred p;\nelect.sync _|p, 0xffffffff;\n@p mbarrier.arrive.shared::cta.b64 _, [%0];\n}" ::"r"(bar) : "memory");
}
__device__ __forceinline__ void mbar_wait(uint32_t bar, uint32_t parity) {
  asm volatile("{\n.reg .pred p;\nWAIT_L:\nmbarrier.try_wait.parity.shared::cta.b64 p, [%0], %1;\n@p bra DONE_L;\nbra WAIT_L;\nDONE_L:\n}"
               ::"r"(bar), "r"(parity) : "memory");
}
__device__ __forceinline__ uint32_t mbar_test(uint32_t bar, uint32_t parity) {
  uint32_t ok;
  asm volatile("{\n.reg .pred p;\nmbarrier.test_wait.parity.shared::cta.b64 p, [%1], %2;\nselp.u32 %0, 1, 0, p;\n}" : "=r"(ok) : "r"(bar), "r"(parity) : "memory");
  return ok;
}
constexpr unsigned long long WATCHDOG_NS = 2000000000ull;
__device__ __forceinline__ unsigned long long gtime() { unsigned long long t; asm volatile("mov.u64 %0, %%globaltimer;" : "=l"(t)); return t; }
__device__ __forceinline__ uint32_t clock32() { uint32_t t; asm volatile("mov.u32 %0, %%clock;" : "=r"(t)); return t; }
__device__ __forceinline__ void mbar_wait_bounded(uint32_t bar, uint32_t parity) {
  unsigned long long t0 = 0;
  for (;;) {
    uint32_t ok;
    asm volatile("{\n.reg .pred p;\nmbarrier.try_wait.parity.shared::cta.b64 p, [%1], %2;\nselp.u32 %0, 1, 0, p;\n}" : "=r"(ok) : "r"(bar), "r"(parity) : "memory");
    if (ok) break;
    const unsigned long long t1 = gtime();
    if (t0 == 0) t0 = t1;
    if (t1 - t0 > WATCHDOG_NS) __trap();
  }
}
__device__ __forceinline__ void tma2d(uint32_t dst, const CUtensorMap* m, int c0, int c1, uint32_t bar) {
  asm volatile("cp.async.bulk.tensor.2d.shared::cluster.global.mbarrier::complete_tx::bytes [%0], [%1, {%3, %4}], [%2];"
               ::"r"(dst), "l"(m), "r"(bar), "r"(c0), "r"(c1) : "memory");
}
__device__ __forceinline__ void tma3d(uint32_t dst, const CUtensorMap* m, int c0, int c1, int c2, uint32_t bar) {
  asm volatile("cp.async.bulk.tensor.3d.shared::cluster.global.mbarrier::complete_tx::bytes [%0], [%1, {%3, %4, %5}], [%2];"
               ::"r"(dst), "l"(m), "r"(bar), "r"(c0), "r"(c1), "r"(c2) : "memory");
}
__device__ __forceinline__ void tma3d_stream(uint32_t dst, const CUtensorMap* m, int c0, int c1, int c2, uint32_t bar) {
  asm volatile("cp.async.bulk.tensor.3d.shared::cluster.global.mbarrier::complete_tx::bytes.L2::cache_hint [%0], [%1, {%3, %4, %5}], [%2], %6;"
               ::"r"(dst), "l"(m), "r"(bar), "r"(c0), "r"(c1), "r"(c2), "l"(0x12F0000000000000ull) : "memory");
}
__device__ __forceinline__ void bulk_load(uint32_t dst, const void* src, uint32_t bytes, uint32_t bar) {
  asm volatile("cp.async.bulk.shared::cluster.global.mbarrier::complete_tx::bytes [%0], [%1], %2, [%3];" ::"r"(dst), "l"(src), "r"(bytes), "r"(bar) : "memory");
}
__device__ __forceinline__ void bulk_store(void* dst, uint32_t src, uint32_t bytes) {
  asm volatile("cp.async.bulk.global.shared::cta.bulk_group [%0], [%1], %2;" ::"l"(dst), "r"(src), "r"(bytes) : "memory");
}
__device__ __forceinline__ void bulk_push(uint32_t dst, uint32_t src, uint32_t bytes, uint32_t bar) {
  asm volatile("cp.async.bulk.shared::cluster.shared::cta.mbarrier::complete_tx::bytes [%0], [%1], %2, [%3];" ::"r"(dst), "r"(src), "r"(bytes), "r"(bar) : "memory");
}
__device__ __forceinline__ void bulk_commit() { asm volatile("cp.async.bulk.commit_group;" ::: "memory"); }
__device__ __forceinline__ void bulk_prefetch(const void* p, uint32_t bytes) {
  asm volatile("cp.async.bulk.prefetch.L2.global [%0], %1;" ::"l"(p), "r"(bytes) : "memory");
}
__device__ __forceinline__ void tma2d_store(const CUtensorMap* m, uint32_t src, int c0, int c1) {
  asm volatile("cp.async.bulk.tensor.2d.global.shared::cta.bulk_group [%0, {%2, %3}], [%1];" ::"l"(m), "r"(src), "r"(c0), "r"(c1) : "memory");
}
__device__ __forceinline__ void wg_fence() { asm volatile("wgmma.fence.sync.aligned;" ::: "memory"); }
__device__ __forceinline__ void wg_commit() { asm volatile("wgmma.commit_group.sync.aligned;" ::: "memory"); }
template <int N> __device__ __forceinline__ void wg_wait() { asm volatile("wgmma.wait_group.sync.aligned %0;" ::"n"(N) : "memory"); }
__device__ __forceinline__ void fence_async_smem() { asm volatile("fence.proxy.async.shared::cta;" ::: "memory"); }
__device__ __forceinline__ void fence_release() { asm volatile("fence.release.gpu;" ::: "memory"); }
__device__ __forceinline__ void fence_acquire() { asm volatile("fence.acquire.gpu;" ::: "memory"); }
__device__ __forceinline__ void nb_sync(int id, int n) { asm volatile("bar.sync %0, %1;" ::"r"(id), "r"(n) : "memory"); }
__device__ __forceinline__ void nb_arrive(int id, int n) { asm volatile("bar.arrive %0, %1;" ::"r"(id), "r"(n) : "memory"); }
__device__ __forceinline__ void stsm4(uint32_t addr, uint32_t r0, uint32_t r1, uint32_t r2, uint32_t r3) {
  asm volatile("stmatrix.sync.aligned.m8n8.x4.shared.b16 [%0], {%1, %2, %3, %4};" ::"r"(addr), "r"(r0), "r"(r1), "r"(r2), "r"(r3) : "memory");
}
__device__ __forceinline__ void sts128(uint32_t addr, uint32_t a, uint32_t b, uint32_t c, uint32_t d) {
  asm volatile("st.shared.v4.b32 [%0], {%1, %2, %3, %4};" ::"r"(addr), "r"(a), "r"(b), "r"(c), "r"(d) : "memory");
}
__device__ __forceinline__ uint32_t pack2(float lo, float hi) {
  uint32_t r; asm("cvt.rn.bf16x2.f32 %0, %1, %2;" : "=r"(r) : "f"(hi), "f"(lo)); return r;
}
__device__ __forceinline__ float bf_lo(uint32_t v) { return __uint_as_float(v << 16); }
__device__ __forceinline__ float bf_hi(uint32_t v) { return __uint_as_float(v & 0xffff0000u); }
__device__ __forceinline__ float bf_round(float v) { return __bfloat162float(__float2bfloat16_rn(v)); }
__device__ __forceinline__ void ldsm4(uint32_t addr, uint32_t (&r)[4]) {
  asm volatile("ldmatrix.sync.aligned.m8n8.x4.shared.b16 {%0, %1, %2, %3}, [%4];" : "=r"(r[0]), "=r"(r[1]), "=r"(r[2]), "=r"(r[3]) : "r"(addr) : "memory");
}
__device__ __forceinline__ uint4 lds128(uint32_t addr) {
  uint4 v; asm volatile("ld.volatile.shared.v4.u32 {%0, %1, %2, %3}, [%4];" : "=r"(v.x), "=r"(v.y), "=r"(v.z), "=r"(v.w) : "r"(addr) : "memory"); return v;
}
__device__ __forceinline__ uint2 lds64(uint32_t addr) { uint2 v; asm volatile("ld.volatile.shared.v2.u32 {%0, %1}, [%2];" : "=r"(v.x), "=r"(v.y) : "r"(addr) : "memory"); return v; }
__device__ __forceinline__ uint32_t lds32(uint32_t addr) { uint32_t v; asm volatile("ld.volatile.shared.u32 %0, [%1];" : "=r"(v) : "r"(addr) : "memory"); return v; }
__device__ __forceinline__ void sts32(uint32_t addr, uint32_t v) { asm volatile("st.shared.u32 [%0], %1;" ::"r"(addr), "r"(v) : "memory"); }
__device__ __forceinline__ uint32_t fma_bf2(uint32_t a, uint32_t b, uint32_t c) { uint32_t r; asm("fma.rn.bf16x2 %0, %1, %2, %3;" : "=r"(r) : "r"(a), "r"(b), "r"(c)); return r; }
__device__ __forceinline__ unsigned ld_relaxed(const unsigned* p) { unsigned v; asm volatile("ld.relaxed.gpu.global.u32 %0, [%1];" : "=r"(v) : "l"(p) : "memory"); return v; }
__device__ __forceinline__ void st_relaxed(unsigned* p, unsigned v) { asm volatile("st.relaxed.gpu.global.u32 [%0], %1;" ::"l"(p), "r"(v) : "memory"); }
__device__ __forceinline__ uint4 ld_relaxed4(const void* p) {
  uint4 v; asm volatile("ld.relaxed.gpu.global.v4.u32 {%0, %1, %2, %3}, [%4];" : "=r"(v.x), "=r"(v.y), "=r"(v.z), "=r"(v.w) : "l"(p) : "memory"); return v;
}
__device__ __forceinline__ float4 ld_relaxed_f4(const void* p) {
  float4 v; asm volatile("ld.relaxed.gpu.global.v4.f32 {%0, %1, %2, %3}, [%4];" : "=f"(v.x), "=f"(v.y), "=f"(v.z), "=f"(v.w) : "l"(p) : "memory"); return v;
}
__device__ __forceinline__ void red_add4(void* p, float a, float b, float c, float d) {
  asm volatile("red.relaxed.gpu.global.add.v4.f32 [%0], {%1, %2, %3, %4};" ::"l"(p), "f"(a), "f"(b), "f"(c), "f"(d) : "memory");
}
__device__ __forceinline__ void red_add(unsigned* p, unsigned v) { asm volatile("red.relaxed.gpu.global.add.u32 [%0], %1;" ::"l"(p), "r"(v) : "memory"); }
__device__ __forceinline__ void wait_counter(const unsigned* p, unsigned target) {
  while (ld_relaxed(p) < target) __nanosleep(32);
  fence_acquire();
}
__device__ __forceinline__ float rcp(float v) { float r; asm("rcp.approx.ftz.f32 %0, %1;" : "=f"(r) : "f"(v)); return r; }
__device__ __forceinline__ float sigmoidf_(float v) { return rcp(1.f + __expf(-v)); }
__device__ __forceinline__ uint32_t phi2(float a, float b, float l2e = 1.4426950408889634f) {
  float ea, eb;
  asm("ex2.approx.ftz.f32 %0, %1;" : "=f"(ea) : "f"(a * l2e));
  asm("ex2.approx.ftz.f32 %0, %1;" : "=f"(eb) : "f"(b * l2e));
  uint32_t t = pack2(a, b), e = pack2(ea, eb), r;
  asm("max.NaN.bf16x2 %0, %0, %1;" : "+r"(t) : "r"(0x35863586u));
  asm("min.bf16x2 %0, %0, %1;" : "+r"(e) : "r"(0x3F803F80u));
  asm("add.rn.bf16x2 %0, %1, %2;" : "=r"(r) : "r"(t), "r"(e));
  return r;
}
__device__ __forceinline__ uint32_t mkdesc(uint32_t addr, uint32_t lbo) { return ((addr & 0x3FFFF) >> 4) | ((lbo >> 4) << 16); }

__device__ __forceinline__ void mma_qkv(float (&d)[96], uint32_t da, uint32_t db, int sc) {
  asm volatile("{\n.reg .pred p;\n.reg .b64 da, db;\nmov.b64 da, {%96, 0x40000040};\nmov.b64 db, {%97, 0x40000040};\nsetp.ne.b32 p, %98, 0;\n"
    "wgmma.mma_async.sync.aligned.m64n192k16.f32.bf16.bf16 "
    "{%0,%1,%2,%3,%4,%5,%6,%7,%8,%9,%10,%11,%12,%13,%14,%15,%16,%17,%18,%19,%20,%21,%22,%23,"
    "%24,%25,%26,%27,%28,%29,%30,%31,%32,%33,%34,%35,%36,%37,%38,%39,%40,%41,%42,%43,%44,%45,%46,%47,"
    "%48,%49,%50,%51,%52,%53,%54,%55,%56,%57,%58,%59,%60,%61,%62,%63,%64,%65,%66,%67,%68,%69,%70,%71,"
    "%72,%73,%74,%75,%76,%77,%78,%79,%80,%81,%82,%83,%84,%85,%86,%87,%88,%89,%90,%91,%92,%93,%94,%95}, "
    "da, db, p, 1, 1, 0, 1;\n}\n"
    : "+f"(d[0]), "+f"(d[1]), "+f"(d[2]), "+f"(d[3]), "+f"(d[4]), "+f"(d[5]), "+f"(d[6]), "+f"(d[7]),
      "+f"(d[8]), "+f"(d[9]), "+f"(d[10]), "+f"(d[11]), "+f"(d[12]), "+f"(d[13]), "+f"(d[14]), "+f"(d[15]),
      "+f"(d[16]), "+f"(d[17]), "+f"(d[18]), "+f"(d[19]), "+f"(d[20]), "+f"(d[21]), "+f"(d[22]), "+f"(d[23]),
      "+f"(d[24]), "+f"(d[25]), "+f"(d[26]), "+f"(d[27]), "+f"(d[28]), "+f"(d[29]), "+f"(d[30]), "+f"(d[31]),
      "+f"(d[32]), "+f"(d[33]), "+f"(d[34]), "+f"(d[35]), "+f"(d[36]), "+f"(d[37]), "+f"(d[38]), "+f"(d[39]),
      "+f"(d[40]), "+f"(d[41]), "+f"(d[42]), "+f"(d[43]), "+f"(d[44]), "+f"(d[45]), "+f"(d[46]), "+f"(d[47]),
      "+f"(d[48]), "+f"(d[49]), "+f"(d[50]), "+f"(d[51]), "+f"(d[52]), "+f"(d[53]), "+f"(d[54]), "+f"(d[55]),
      "+f"(d[56]), "+f"(d[57]), "+f"(d[58]), "+f"(d[59]), "+f"(d[60]), "+f"(d[61]), "+f"(d[62]), "+f"(d[63]),
      "+f"(d[64]), "+f"(d[65]), "+f"(d[66]), "+f"(d[67]), "+f"(d[68]), "+f"(d[69]), "+f"(d[70]), "+f"(d[71]),
      "+f"(d[72]), "+f"(d[73]), "+f"(d[74]), "+f"(d[75]), "+f"(d[76]), "+f"(d[77]), "+f"(d[78]), "+f"(d[79]),
      "+f"(d[80]), "+f"(d[81]), "+f"(d[82]), "+f"(d[83]), "+f"(d[84]), "+f"(d[85]), "+f"(d[86]), "+f"(d[87]),
      "+f"(d[88]), "+f"(d[89]), "+f"(d[90]), "+f"(d[91]), "+f"(d[92]), "+f"(d[93]), "+f"(d[94]), "+f"(d[95])
    : "r"(da), "r"(db), "r"(sc));
}

__device__ __forceinline__ void mma_out(float (&d)[64], uint32_t da, uint32_t db, int sc) {
  asm volatile("{\n.reg .pred p;\n.reg .b64 da, db;\nmov.b64 da, {%64, 0x40000040};\nmov.b64 db, {%65, 0x40000040};\nsetp.ne.b32 p, %66, 0;\n"
    "wgmma.mma_async.sync.aligned.m64n128k16.f32.bf16.bf16 "
    "{%0,%1,%2,%3,%4,%5,%6,%7,%8,%9,%10,%11,%12,%13,%14,%15,%16,%17,%18,%19,%20,%21,%22,%23,"
    "%24,%25,%26,%27,%28,%29,%30,%31,%32,%33,%34,%35,%36,%37,%38,%39,%40,%41,%42,%43,%44,%45,%46,%47,"
    "%48,%49,%50,%51,%52,%53,%54,%55,%56,%57,%58,%59,%60,%61,%62,%63}, "
    "da, db, p, 1, 1, 0, 1;\n}\n"
    : "+f"(d[0]), "+f"(d[1]), "+f"(d[2]), "+f"(d[3]), "+f"(d[4]), "+f"(d[5]), "+f"(d[6]), "+f"(d[7]),
      "+f"(d[8]), "+f"(d[9]), "+f"(d[10]), "+f"(d[11]), "+f"(d[12]), "+f"(d[13]), "+f"(d[14]), "+f"(d[15]),
      "+f"(d[16]), "+f"(d[17]), "+f"(d[18]), "+f"(d[19]), "+f"(d[20]), "+f"(d[21]), "+f"(d[22]), "+f"(d[23]),
      "+f"(d[24]), "+f"(d[25]), "+f"(d[26]), "+f"(d[27]), "+f"(d[28]), "+f"(d[29]), "+f"(d[30]), "+f"(d[31]),
      "+f"(d[32]), "+f"(d[33]), "+f"(d[34]), "+f"(d[35]), "+f"(d[36]), "+f"(d[37]), "+f"(d[38]), "+f"(d[39]),
      "+f"(d[40]), "+f"(d[41]), "+f"(d[42]), "+f"(d[43]), "+f"(d[44]), "+f"(d[45]), "+f"(d[46]), "+f"(d[47]),
      "+f"(d[48]), "+f"(d[49]), "+f"(d[50]), "+f"(d[51]), "+f"(d[52]), "+f"(d[53]), "+f"(d[54]), "+f"(d[55]),
      "+f"(d[56]), "+f"(d[57]), "+f"(d[58]), "+f"(d[59]), "+f"(d[60]), "+f"(d[61]), "+f"(d[62]), "+f"(d[63])
    : "r"(da), "r"(db), "r"(sc));
}

__device__ __forceinline__ void mma_ktv(float (&d)[36], uint32_t da, uint32_t db, int sc) {
  asm volatile("{\n.reg .pred p;\n.reg .b64 da, db;\nmov.b64 da, {%36, 0x40000040};\nmov.b64 db, {%37, 0x40000040};\nsetp.ne.b32 p, %38, 0;\n"
    "wgmma.mma_async.sync.aligned.m64n72k16.f32.bf16.bf16 "
    "{%0,%1,%2,%3,%4,%5,%6,%7,%8,%9,%10,%11,%12,%13,%14,%15,%16,%17,%18,%19,%20,%21,%22,%23,"
    "%24,%25,%26,%27,%28,%29,%30,%31,%32,%33,%34,%35}, "
    "da, db, p, 1, 1, 1, 1;\n}\n"
    : "+f"(d[0]), "+f"(d[1]), "+f"(d[2]), "+f"(d[3]), "+f"(d[4]), "+f"(d[5]), "+f"(d[6]), "+f"(d[7]),
      "+f"(d[8]), "+f"(d[9]), "+f"(d[10]), "+f"(d[11]), "+f"(d[12]), "+f"(d[13]), "+f"(d[14]), "+f"(d[15]),
      "+f"(d[16]), "+f"(d[17]), "+f"(d[18]), "+f"(d[19]), "+f"(d[20]), "+f"(d[21]), "+f"(d[22]), "+f"(d[23]),
      "+f"(d[24]), "+f"(d[25]), "+f"(d[26]), "+f"(d[27]), "+f"(d[28]), "+f"(d[29]), "+f"(d[30]), "+f"(d[31]),
      "+f"(d[32]), "+f"(d[33]), "+f"(d[34]), "+f"(d[35])
    : "r"(da), "r"(db), "r"(sc));
}

__device__ __forceinline__ void mma_qkvz(float (&d)[20], const uint32_t (&a)[4], uint32_t db, int sc) {
  asm volatile("{\n.reg .pred p;\n.reg .b64 db;\nmov.b64 db, {%24, 0x20};\nsetp.ne.b32 p, %25, 0;\n"
    "wgmma.mma_async.sync.aligned.m64n40k16.f32.bf16.bf16 "
    "{%0,%1,%2,%3,%4,%5,%6,%7,%8,%9,%10,%11,%12,%13,%14,%15,%16,%17,%18,%19}, "
    "{%20,%21,%22,%23}, db, p, 1, 1, 1;\n}\n"
    : "+f"(d[0]), "+f"(d[1]), "+f"(d[2]), "+f"(d[3]), "+f"(d[4]), "+f"(d[5]), "+f"(d[6]), "+f"(d[7]),
      "+f"(d[8]), "+f"(d[9]), "+f"(d[10]), "+f"(d[11]), "+f"(d[12]), "+f"(d[13]), "+f"(d[14]), "+f"(d[15]),
      "+f"(d[16]), "+f"(d[17]), "+f"(d[18]), "+f"(d[19])
    : "r"(a[0]), "r"(a[1]), "r"(a[2]), "r"(a[3]), "r"(db), "r"(sc));
}

struct Params {
  CUtensorMap x, w, xr, wo, out, gate, up, down;
};

__device__ __forceinline__ void fma8(float (&acc)[8], const uint4& w, float m) {
  acc[0] = fmaf(bf_lo(w.x), m, acc[0]); acc[1] = fmaf(bf_hi(w.x), m, acc[1]);
  acc[2] = fmaf(bf_lo(w.y), m, acc[2]); acc[3] = fmaf(bf_hi(w.y), m, acc[3]);
  acc[4] = fmaf(bf_lo(w.z), m, acc[4]); acc[5] = fmaf(bf_hi(w.z), m, acc[5]);
  acc[6] = fmaf(bf_lo(w.w), m, acc[6]); acc[7] = fmaf(bf_hi(w.w), m, acc[7]);
}
__device__ __forceinline__ float butterfly8(float (&s)[8], int lane, int o) {
#pragma unroll
  for (int k = 1; k < 8; k <<= 1) {
    const bool up = lane & (o * k);
#pragma unroll
    for (int j = 0; j < 4 / k; j++) s[j] = (up ? s[2 * j + 1] : s[2 * j]) + __shfl_xor_sync(~0u, up ? s[2 * j] : s[2 * j + 1], o * k);
  }
  return s[0];
}
constexpr int PEER = 9;
constexpr __host__ __device__ uint32_t step_list() {
  uint32_t r = 0;
  for (int j = PEER - 1; j >= 0; j--) if (j != OWN) r = r << 4 | j % 5 | (j < 5) << 3;
  return r;
}
template <bool BY_SM> struct Tile {
  int sm, tm, tn, mu;
  bool spare;
  __device__ __forceinline__ Tile() {
    if (BY_SM) asm volatile("mov.u32 %0, %%smid;" : "=r"(sm));
    else sm = blockIdx.x + (blockIdx.x >= 120) * 4;
    const int tp = sm >> 1, pr = sm & 1;
    const int v = tp < 32 ? tp : tp < 60 ? (tp * 293 - 928) >> 8 : tp * 8 - 464, g = v & 7, i = v >> 3;
    const int j = i * 11 >> 5, c = i - j * 3;
    tm = (v & 6) * 2 + (c < 2 ? j : 3); tn = (GMK * 4 >> g & 4) + (c < 2 ? c : j) * 2 + pr;
    mu = i == NOMOD ? 112 : g * 14 + (i - (i > NOMOD)) * 2 + pr;
    spare = (tp | 1) == 61;
  }
};

template <bool BY_SM> __global__ void __cluster_dims__(2, 1, 1) __launch_bounds__(NTHREADS, 1)
fused_kernel(const __nv_bfloat16* __restrict__ px, Scratch* gs, void* pout, const __nv_bfloat16* __restrict__ w_r, const __nv_bfloat16* __restrict__ gate_w,
             const __nv_bfloat16* __restrict__ w_gate, const __grid_constant__ Params p, const __nv_bfloat16* __restrict__ w_up) {
  extern __shared__ __align__(1024) uint8_t smem[];
  const uint32_t sb = __shfl_sync(~0u, (uint32_t)__cvta_generic_to_shared(smem), 0);
  const int tid = threadIdx.x, lane = tid & 31;
  const int warp = __shfl_sync(~0u, tid >> 5, 0), wg = warp >> 2;
  const uint32_t t_start = clock32();
  const Tile<BY_SM> tile;
  const int tm = tile.tm, tn = tile.tn, mu = tile.mu, cta = tm * 8 + tn;
  {
    const uint32_t cnt = (uint32_t)((warp & 8 ? bar_counts(16) : bar_counts(0)) >> (warp & 7) * 8);
    if (elect()) mbar_init(sb + OFF_BAR + warp * 16, cnt & 15);
    if (elect()) mbar_init(sb + OFF_BAR + warp * 16 + 8, cnt >> 4 & 15);
    if (elect()) mbar_init(sb + BAR_LAND + warp * 8, 1);
    asm volatile("fence.mbarrier_init.release.cluster;" ::: "memory");
  }
  if (warp == 0 && !tile.spare) {
#pragma unroll
    for (int s = 0; s < PRE; s++) {
      if (elect()) tma3d(sb + OFF_RING + s * STAGE_BYTES + A_BYTES, &p.w, tn * 64, s * 64, 0, sb + BAR_FULL + s * 8);
      if (elect()) tma2d(sb + OFF_RING + s * STAGE_BYTES, &p.x, s * 64, tm * 128, sb + BAR_FULL + s * 8);
      PROF_P(lane == 0, 64 + s);
    }
    if (elect()) {
#pragma unroll
      for (int s = 0; s < PRE; s++) { mbar_expect_tx(sb + BAR_FULL + s * 8, STAGE_BYTES); mbar_arrive(sb + BAR_FULL + s * 8); }
    }
  }
  asm volatile("" ::: "memory");
  if (warp == 5) {
#pragma unroll
    for (int i = 0; i < 4; i++) sts128(sb + OFF_ONES + i * 512 + lane * 16, 0x3F803F80u, 0x3F803F80u, 0x3F803F80u, 0x3F803F80u);
    sts32(sb + OFF_MISC + 20, 0x3FB8AA3Bu);
    fence_async_smem();
  }
  __syncthreads();
  if (tile.spare) {
    if (warp == 0) {
      const unsigned tag = (ld_relaxed(&gs->spare[tile.sm & 3]) + 1) & 0xFFF;
      const unsigned long long t0 = gtime();
      uint4 r4;
      do {
        __nanosleep(2048);
        if (gtime() - t0 > WATCHDOG_NS) __trap();
        r4 = ld_relaxed4(&gs->rslot[tile.sm & 3][lane * 4]);
      } while (!__all_sync(~0u, (((r4.x ^ tag) | (r4.y ^ tag) | (r4.z ^ tag) | (r4.w ^ tag)) & 0xFFF) == 0));
      if (tid == 0) st_relaxed(&gs->spare[tile.sm & 3], tag);
    }
    return;
  }

  if (wg == 3) {
    asm volatile("setmaxnreg.dec.sync.aligned.u32 24;");
    if (warp == 12) {
      mbar_wait(sb + BAR_W31, 0);
      mbar_wait(sb + BAR_IDX, 0);
      const uint32_t lowb = (1u << (tn & 6) * 4) - 1;
      uint32_t slabs = 0x76543210u, steps = step_list();
      const uint4* src = gs->o[tm][0];
      unsigned seen = 0;
#pragma unroll 1
      for (int n = 8; n >= 6; n -= 2) {
#pragma unroll 1
        for (int i = 0; i < n; i++, slabs >>= 4, steps >>= 4) {
          const uint32_t s = steps & 7, full = sb + BAR_FULL + s * 8, need = 4u << (slabs & 7) * 4;
          const uint32_t land = n == 8 ? full : sb + BAR_LAND + i * 8;
          mbar_wait(full + (BAR_EMPTY - BAR_FULL), steps >> 3 & 1);
          PROF(lane == 0 && (!PROFC || n == 6), 224 + i + (n == 6) * 10);
          if (!__all_sync(~0u, seen & need)) {
            while (!__all_sync(~0u, (seen = ld_relaxed(gs->cnt[tm])) & need)) __nanosleep(FSL);
          }
          if (elect()) bulk_load(sb + OFF_RING + s * O_BYTES, src + (slabs & 7) * 1024, A_BYTES, land);
          if (elect()) mbar_expect_tx(land, A_BYTES);
          PROF(lane == 0 && (!PROFC || n == 6), 240 + i + (n == 6) * 10);
        }
        slabs = (0x76543210u & lowb) | (0x765432u & ~lowb);
        steps = 0x0CBA98u;
        src += 8 * 1024;
      }
    } else if (warp == 13) {
      uint32_t full = sb + BAR_FULL + PRE * 8, dst = sb + OFF_RING + PRE * STAGE_BYTES + A_BYTES, c0 = tn * 64, c1 = PRE * 64;
#pragma unroll 1
      for (int g = PRE; g < 32; g++) {
        if (g < 4) while ((int)(clock32() - t_start) < g * ST1) {}
        const bool reuse = (g >> 2) == 4;
        mbar_wait(full + (BAR_EMPTY - BAR_FULL), ((g >> 2) & 1) ^ 1);
        if (!reuse && elect()) tma2d(dst - A_BYTES, &p.x, c1, tm * 128, full);
        if (elect()) tma3d(dst, &p.w, c0, c1, 0, full);
        if (elect()) { mbar_expect_tx(full, reuse ? BQ_BYTES : STAGE_BYTES); mbar_arrive(full); }

        PROF_P(lane == 0, 64 + g);
        const uint32_t i = g - RT_G0;
        if (i < 4 && elect()) {
          mbar_expect_tx(sb + BAR_RT + i * 8, i ? 8192 : 8192 + 4096);
          tma2d(sb + OFF_PK + i * 8192, &p.xr, (RT_ORD >> i * 4 & 3) * 256, cta * 16, sb + BAR_RT + i * 8);
          if (i == 0) { bulk_load(sb + OFF_KVB, w_r, 2048, sb + BAR_RT); bulk_load(sb + OFF_KVB + 2048, gate_w, 2048, sb + BAR_RT); }
        }
        const uint32_t c = g - MOD_START;
        if (c == MOD_BUFS) mbar_wait(sb + BAR_RTD, 0);
        if (c < MOD_BUFS0 && mu < MOD_CTAS && elect()) {
          PROF_P(true, 192 + c);
          const uint32_t mfull = sb + BAR_MFULL + c * 8, mdst = sb + OFF_MOD + c * 8192;
          mbar_expect_tx(mfull, c ? 8192 : 8192 + 2048);
          tma3d(mdst, &p.gate, mu * 32, c * 16, 0, mfull); tma3d(mdst + 4096, &p.up, mu * 32, c * 16, 0, mfull);
        }
        const uint32_t pc = g - PF_MOD;
        if (pc < 16 && elect()) bulk_prefetch((cta & 64 ? w_up : w_gate) + (size_t)(pc * 64 + (cta & 63)) * F_, F_ * 2);
        full += 8; dst += STAGE_BYTES; c1 += 64;
        if ((g & 3) == 3) { full -= 32; dst -= 4 * STAGE_BYTES; }
        if (g == 15) { c0 += 512; c1 = 768; }
        if (g == 19) c1 = 0;
      }
      mbar_arrive_warp(sb + BAR_W31);
      const uint32_t lowb = (1u << (tn & 6) * 4) - 1;
      uint64_t slabs = (uint64_t)((0xFEDCBA98u & lowb) | (0xFEDCBAu & ~lowb)) << 40 | (uint64_t)(8 + (tn ^ 1)) << 36 | (uint64_t)(8 + tn) << OWN * 4 |
                       (0x76543210ull & ~(~0ull << OWN * 4)) | (0x765432100ull & ~0ull << (OWN * 4 + 4));
      uint32_t ph = 1;
      c1 = 0;
#pragma unroll 1
      for (int g = 0; g < 16; g++) {
        mbar_wait(full + (BAR_EMPTY - BAR_FULL), ph);
        if (elect()) tma3d(dst, &p.wo, 0, c1, tn * 2, full);
        if (elect()) mbar_expect_tx(full, BO_BYTES);
        PROF_P(lane == 0, 96 + g);
        if (g == OWN && elect()) mbar_arrive(full);
        full += 8; dst += O_BYTES; slabs >>= 4; c1 = ((uint32_t)slabs & 15) * 64;
        if (full == sb + BAR_EMPTY) { full -= 40; dst -= 5 * O_BYTES; ph ^= 1; }
      }
    } else if (warp == 14) {
      if (mu < MOD_CTAS) {
        uint32_t full = sb + BAR_MFULL, dst = sb + OFF_MOD, ph = 0;
#pragma unroll 1
        for (int c = MOD_BUFS0; c < 24; c++) {
          mbar_wait(full + (BAR_MEMPTY - BAR_MFULL), ph);
          PROF_P(lane == 0, 192 + c);
          if (c < 16) {
            if (elect()) { tma3d(dst, &p.gate, mu * 32, c * 16, 0, full); tma3d(dst + 4096, &p.up, mu * 32, c * 16, 0, full); }
          } else if (elect()) tma3d_stream(dst, &p.down, 0, mu * 32 + (c - 16) * 4, 0, full);
          if (elect()) mbar_expect_tx(full, 8192);
          full += 8; dst += 8192;
          if (dst == sb + OFF_PK) { full -= MOD_BUFS * 8; dst = sb + OFF_MOD; ph ^= 1; }
        }
      }
      if (elect()) {
      mbar_wait(sb + BAR_IDX, 0);
      const bool paired = lds32(sb + OFF_MISC + 28) < 0x200;
      const uint32_t pb = peer_addr(sb);
      mbar_wait(sb + BAR_EMPTY + PEER % 5 * 8, 0);
      mbar_expect_tx(sb + BAR_FULL + PEER % 5 * 8, A_BYTES);
      if (paired) mbar_arrive_peer(pb + BAR_PA);
      mbar_wait(sb + BAR_OST, 0);
      mbar_expect_tx(sb + BAR_X, 32768);
      tma2d(sb + OFF_PK, &p.x, tn * 128, tm * 128, sb + BAR_X);
      tma2d(sb + OFF_V, &p.x, tn * 128 + 64, tm * 128, sb + BAR_X);
      if (paired) {
        mbar_wait(sb + BAR_PA, 0);
        mbar_wait(sb + BAR_OWN, 0);
        bulk_push(pb + OFF_RING + PEER % 5 * O_BYTES, sb + OFF_MOD, A_BYTES, pb + BAR_FULL + PEER % 5 * 8);
        mbar_wait(sb + BAR_EMPTY + PEER % 5 * 8, 1);
        mbar_arrive_peer(pb + BAR_PA);
        mbar_wait(sb + BAR_PA, 1);
      } else {
        mbar_wait(sb + BAR_EMPTY + OWN % 5 * 8, 1);
        bulk_load(sb + OFF_RING + PEER % 5 * O_BYTES, gs->o[tm][8 + (tn ^ 1)], A_BYTES, sb + BAR_FULL + PEER % 5 * 8);
      }
      }
    } else if (elect()) {
#pragma unroll 1
      for (int i = 2; i < 8; i++) asm volatile("prefetch.tensormap [%0];" ::"l"(&p.x + i) : "memory");
      mbar_wait_bounded(sb + BAR_DONE, 0);
    }
  } else if (wg == 2) {
    asm volatile("setmaxnreg.dec.sync.aligned.u32 40;");
    const int mw = warp & 3;
    if (mw == 0) {
      const unsigned tag = (ld_relaxed(&gs->rslot[tn][cta]) + 1) & 0xFFF;
#pragma unroll
      for (int i = 0; i < 4; i++)
        if (lane < NCLR) ((float4*)gs)[cta * (NCLR * 4) + i * NCLR + lane] = make_float4(0.f, 0.f, 0.f, 0.f);
      if (lane == 29) st_relaxed(&gs->block[cta], blockIdx.x << 12 | tag);
      fence_release();
      nb_sync(NB_KEY, 160);
      const uint4 k4 = lds128(sb + OFF_MISC);
      if (lane < 8) st_relaxed(&gs->rslot[lane][cta], max(max(k4.x, k4.y), max(k4.z, k4.w)) | tag);
      if (lane < 16) st_relaxed(&gs->gslot[cta * 16 + lane], lds32(sb + OFF_G + lane * 4) | tag);
      PROF(lane == 0, 20);
      uint4 r4;
      do {
        __nanosleep(RT_SLEEP);
        r4 = ld_relaxed4(&gs->rslot[tn][lane * 4]);
      } while (!__all_sync(~0u, (((r4.x ^ tag) | (r4.y ^ tag) | (r4.z ^ tag) | (r4.w ^ tag)) & 0xFFF) == 0));
      const int c0 = 0xFFF0 - lane * 64;
      unsigned key = max(max((r4.x & 0xFFFF0000u) | (c0 + ((r4.x >> 12) & 15)), (r4.y & 0xFFFF0000u) | (c0 - 16 + ((r4.y >> 12) & 15))),
                         max((r4.z & 0xFFFF0000u) | (c0 - 32 + ((r4.z >> 12) & 15)), (r4.w & 0xFFFF0000u) | (c0 - 48 + ((r4.w >> 12) & 15))));
      key = __reduce_max_sync(~0u, key);
      if (elect()) {
        sts32(sb + OFF_MISC + 16, key);
        sts32(sb + OFF_MISC + 24, tag & 1);
        if (mu < MOD_CTAS) bulk_load(sb + OFF_XSEL, px + (size_t)(0xFFFF - (key & 0xFFFF)) * D_, 2048, sb + BAR_MFULL);
      }
      PROF(lane == 0, 21);
      unsigned nb;
      do {
        r4 = ld_relaxed4(&gs->gslot[tm * 128 + lane * 4]);
        nb = ld_relaxed(&gs->block[cta ^ 1]);
      } while (!__all_sync(~0u, (((r4.x ^ tag) | (r4.y ^ tag) | (r4.z ^ tag) | (r4.w ^ tag) | (nb ^ tag)) & 0xFFF) == 0));
      sts128(sb + OFF_G + lane * 16, r4.x & 0xFFFF0000u, r4.y & 0xFFFF0000u, r4.z & 0xFFFF0000u, r4.w & 0xFFFF0000u);
      sts32(sb + OFF_MISC + 28, (PAIRED && nb >> 12 == (blockIdx.x ^ 1) ? 0x1FF : 0x3FF) & ~((1 << PC) - 1 | 1 << OWN));
      fence_acquire();
      __syncwarp();
      mbar_arrive_warp(sb + BAR_IDX);
    }
    PROF(tid == 256, 22);
    if (mu >= MOD_CTAS) {
      mbar_arrive_warp(sb + BAR_IDX);
      mbar_arrive_warp(sb + BAR_OA);
    } else {
      const uint32_t wp = sb + OFF_MOD + (mw >> 1) * 4096 + (mw & 1) * 512 + lane * 16;
      uint32_t mp = sb + OFF_XSEL - 128 + (mw & 1) * 64 + (lane >> 2) * 8, mc = 128;
      float acc[8] = {0.f, 0.f, 0.f, 0.f, 0.f, 0.f, 0.f, 0.f};
      uint32_t b = ~0u, ph = 0, a = sb + OFF_ONES - 3072;
      float m3 = 0.f;
      const uint32_t zero = lds32(sb + OFF_ONES) & 1;
      uint2 m = make_uint2(0, 0);
      uint4 w0 = make_uint4(0, 0, 0, 0), w1 = w0, w2 = w0, w3 = w0;
#pragma unroll 1
      for (int c = -1;; c++) {
        fma8(acc, w3, m3);
        w3 = lds128(a + 3072);
        const uint32_t rel = sb + BAR_MEMPTY + b * 8;
        if (c == 16) {
          const uint32_t ft = fresh_tid(), fl = ft & 31;
          sts32(sb + OFF_PART + (ft & 96) * 4 + ((ft & 3) * 8 + (fl >> 2)) * 4, __float_as_uint(butterfly8(acc, fl, 4)));
          nb_sync(NB_MODW, 128);
          const float* part = (const float*)(smem + OFF_PART) + fl;
          const float gp = bf_round(part[0] + part[32]), up = bf_round(part[64] + part[96]);
          *(__nv_bfloat16*)(smem + OFF_PART + 512 + fl * 2) = __float2bfloat16_rn(bf_round(gp * sigmoidf_(gp)) * up);
          __syncwarp();
          mp = sb + OFF_PART + 512; mc = 8;
          m = lds64(mp);
#pragma unroll
          for (int i = 0; i < 8; i++) acc[i] = 0.f;
          PROF(lane == 0 && mw == 0, 23);
        }
        if (++b == (c < MOD_BUFS0 ? MOD_BUFS0 : MOD_BUFS)) { b = 0; ph ^= 1; }
        const uint32_t ok = mbar_test(sb + BAR_MFULL + b * 8, ph);
        fma8(acc, w0, bf_lo(m.x));
        if (c >= 0) mbar_arrive_warp(rel + ((w3.x | __float_as_uint(acc[7])) & zero));
        fma8(acc, w1, bf_hi(m.x));
        fma8(acc, w2, bf_lo(m.y));
        m3 = bf_hi(m.y);
        if (c == 23) break;
        if (!ok) mbar_wait(sb + BAR_MFULL + b * 8, ph);
        a = wp + b * 8192;
        mp += mc;
        m = lds64(mp);
        w0 = lds128(a); w1 = lds128(a + 1024); w2 = lds128(a + 2048);
      }
      fma8(acc, w3, m3);
      mbar_arrive_warp(sb + BAR_OA);
      float* yacc = gs->y[tn] + (fresh_tid() & 127) * 8;
      red_add4(yacc, acc[0], acc[1], acc[2], acc[3]);
      red_add4(yacc + 4, acc[4], acc[5], acc[6], acc[7]);
      PROF(lane == 0 && mw == 0, 25);
      nb_sync(NB_MODW, 128);
      if (mw == 0 && elect()) { fence_release(); red_add(gs->cnt[32], 1); }
      PROF(lane == 0 && mw == 0, 24);
    }
    const unsigned key = lds32(sb + OFF_MISC + 16);
    const int sel = 0xFFFF - (int)(key & 0xFFFF) - tm * 128;
    if (mw == 0 && sel >= 0 && sel < 128) {
      if (elect()) wait_counter(gs->cnt[32], MOD_CTAS);
      __syncwarp();
      const unsigned k16 = key >> 16;
      const float rs = bf_round(sigmoidf_(__uint_as_float(((k16 & 0x8000u) ? (k16 & 0x7FFFu) : (~k16 & 0xFFFFu)) << 16)));
      float4 v = make_float4(0.f, 0.f, 0.f, 0.f);
#pragma unroll 4
      for (int i = 0; i < 8; i++) {
        const float4 u = ld_relaxed_f4(gs->y[i] + tn * 128 + lane * 4);
        v.x += u.x; v.y += u.y; v.z += u.z; v.w += u.w;
      }
      mbar_wait(sb + BAR_X, 0);
      uint2* xp = (uint2*)(smem + OFF_PK + (lane >> 4) * 16384 + sel * 128 + ((((lane >> 1) & 7) ^ (sel & 7)) << 4) + (lane & 1) * 8);
      const uint2 xv = *xp;
      *xp = make_uint2(pack2(bf_lo(xv.x) + bf_round(bf_round(v.x) * rs), bf_hi(xv.x) + bf_round(bf_round(v.y) * rs)),
                       pack2(bf_lo(xv.y) + bf_round(bf_round(v.z) * rs), bf_hi(xv.y) + bf_round(bf_round(v.w) * rs)));
      __syncwarp();
      mbar_arrive_warp(sb + BAR_Y);
    }
  } else {
    asm volatile("setmaxnreg.inc.sync.aligned.u32 224;");
    const int w = warp & 3, wt = tid & 127;
    const int nb_self = NB_WG0 + wg;
    const uint32_t da0 = mkdesc(sb + OFF_RING, 16), db0 = mkdesc(sb + OFF_RING + A_BYTES, 8192);

    if (wg == 1) {
      float s[8] = {0.f, 0.f, 0.f, 0.f, 0.f, 0.f, 0.f, 0.f};
      const uint32_t zero = lds32(sb + OFF_ONES) & 1;
      uint32_t mask = 0xffff0000u;
#pragma unroll 1
      for (int i = 0; i < 4; i++) {
        const uint32_t u = RT_ORD >> i * 4 & 3;
        mbar_wait(sb + BAR_RT + i * 8, 0);
        const uint4 wr = lds128(sb + OFF_KVB + u * 512 + lane * 16), gw = lds128(sb + OFF_KVB + 2048 + u * 512 + lane * 16);
        uint4 xv[4];
#pragma unroll
        for (int r = 0; r < 4; r++) xv[r] = lds128(sb + OFF_PK + i * 8192 + (w * 4 + r) * 512 + lane * 16);
        const float wf[16] = {bf_lo(wr.x), bf_hi(wr.x), bf_lo(wr.y), bf_hi(wr.y), bf_lo(wr.z), bf_hi(wr.z), bf_lo(wr.w), bf_hi(wr.w),
                              bf_lo(gw.x), bf_hi(gw.x), bf_lo(gw.y), bf_hi(gw.y), bf_lo(gw.z), bf_hi(gw.z), bf_lo(gw.w), bf_hi(gw.w)};
#pragma unroll
        for (int r = 0; r < 4; r++) {
          const uint4 xq = xv[r];
          const float xf[8] = {bf_lo(xq.x), __uint_as_float(xq.x & mask), bf_lo(xq.y), bf_hi(xq.y), bf_lo(xq.z), bf_hi(xq.z), bf_lo(xq.w), bf_hi(xq.w)};
#pragma unroll
          for (int j = 0; j < 8; j++) { s[2 * r] = fmaf(xf[j ^ 1], wf[j ^ 1], s[2 * r]); s[2 * r + 1] = fmaf(xf[j ^ 1], wf[8 + (j ^ 1)], s[2 * r + 1]); }
          mask = ((__float_as_uint(s[2 * r]) | __float_as_uint(s[2 * r + 1])) & zero) | 0xffff0000u;
        }
      }
      mbar_arrive_warp(sb + BAR_RTD);
      float v = butterfly8(s, lane, 1);
      PROF_C(wt == 0 && v != 12345.f, 19);
      v += __shfl_xor_sync(~0u, v, 8);
      v = bf_round(v + __shfl_xor_sync(~0u, v, 16));
      const unsigned rb = __float_as_uint(v) >> 16, row = w * 4 + ((lane & 7) >> 1);
      unsigned key = (lane & 1) ? 0u : ((((rb & 0x8000u) ? (~rb & 0xFFFFu) : (rb | 0x8000u)) << 16) | ((15 - row) << 12));
      key = __reduce_max_sync(~0u, key);
      if (lane == 0) sts32(sb + OFF_MISC + w * 4, key);
      if (lane < 8 && (lane & 1)) sts32(sb + OFF_G + row * 4, __float_as_uint(bf_round(sigmoidf_(v))));
      nb_arrive(NB_KEY, 160);
      nb_sync(NB_ORDER_AB, 256);
    }

    uint32_t pq[2][4][4];
    float4* const kvacc = &gs->kv[wg][tn][0][wt];
    {
      float acc[2][96];
      PROF_C(wt == 0, 1 + wg * 8);
#pragma unroll 1
      for (int g = 0; g < 14; g++) {
        const uint32_t s = g & 3;
        const uint32_t da = da0 + s * (STAGE_BYTES >> 4), db = db0 + s * (STAGE_BYTES >> 4);
        mbar_wait(sb + BAR_FULL + s * 8, (g >> 2) & 1);
        PROF_C(wt == 0, 64 + wg * 16 + g);
#pragma unroll
        for (int m = 0; m < 2; m++) {
          wg_fence();
#pragma unroll
          for (int kk = 0; kk < 4; kk++) mma_qkv(acc[m], da + (m * 512 + kk * 2), db + kk * 128, kk ? 1 : g);
          wg_commit();
          if (m == 0) {
            wg_wait<1>();
            if (g) mbar_arrive_warp(sb + BAR_EMPTY + ((g + 3) & 3) * 8);
          }
        }
      }
      auto half_step = [&](int m, int g) {
        wg_fence();
#pragma unroll
        for (int kk = 0; kk < 4; kk++)
          mma_qkv(acc[m], da0 + ((g & 3) * (STAGE_BYTES >> 4) + m * 512 + kk * 2), db0 + ((g & 3) * (STAGE_BYTES >> 4) + kk * 128), 1);
        wg_commit();
      };
#pragma unroll
      for (int g = 14; g < 16; g++) {
        mbar_wait(sb + BAR_FULL + (g & 3) * 8, 1);
        PROF_C(wt == 0, 64 + wg * 16 + g);
        half_step(0, g);
        if (g == 14) { wg_wait<1>(); mbar_arrive_warp(sb + BAR_EMPTY + ((g + 3) & 3) * 8); }
      }
      half_step(1, 14);
      half_step(1, 15);
      if (wg == 0) nb_arrive(NB_ORDER_AB, 256);
      mbar_wait(sb + BAR_IDX, 0);
      if (wg == 1) nb_sync(NB_STG, 256);
      wg_wait<2>();
      PROF_C(wt == 0, 3 + wg * 8);

      const uint32_t st_row = (uint32_t)(w * 16 + (lane & 15)) * 128;
      float c[36];
      const uint32_t dk = mkdesc(sb + OFF_PK, 16), dv = mkdesc(sb + OFF_V, OFF_ONES - OFF_V);
      uint32_t l2k[8 + PA];
#pragma unroll
      for (int u = 0; u < PA; u++) l2k[u] = 0x3FB8AA3Bu;
#pragma unroll
      for (int u = 0; u < 8; u++) {
        const int m = u >> 2, j = u & 3;
        const uint32_t a = sb + m * 8192 + st_row + ((((lane >> 4) + 2 * j) ^ (lane & 7)) << 4);
        const float* k = &acc[m][32 + 8 * j];
        const float l = __uint_as_float(l2k[u]);
        if (u == M1) {
          wg_wait<1>();
          mbar_arrive_warp(sb + BAR_EMPTY + 2 * 8);
        }
        if (u == MM) {
          wg_wait<0>();
          mbar_arrive_warp(sb + BAR_EMPTY + 3 * 8);
        }
        const float* v = &acc[m][64 + 8 * j];
        stsm4(a + OFF_V, pack2(v[0], v[1]), pack2(v[2], v[3]), pack2(v[4], v[5]), pack2(v[6], v[7]));
        const uint32_t r0 = phi2(k[0], k[1], l), r1 = phi2(k[2], k[3], l), r2 = phi2(k[4], k[5], l), r3 = phi2(k[6], k[7], l);
        stsm4(a + OFF_PK, r0, r1, r2, r3);
        if (u + PA < 8) l2k[u + PA] = lds32(sb + OFF_MISC + 20);
      }
      fence_async_smem();
      nb_sync(nb_self, 128);
      PROF_C(wt == 0, 8 + wg * 8);
      wg_fence();
#pragma unroll
      for (int kk = 0; kk < 8; kk++) mma_ktv(c, dk + kk * 128, dv + (kk * 128 - (kk << 23)), kk ? 1 : 0);
      wg_commit();
      if (wg == 1) nb_arrive(NB_ORDER_BO, 256);
      auto reduce = [&](float4* dst, int gap) {
        wg_wait<0>();
        PROF_C(wt == 0, 4 + wg * 8);
        float u[18];
#pragma unroll
        for (int i = 0; i < 16; i++) u[i] = w >= 2 ? c[16 + i] : c[i];
        u[16] = __shfl_down_sync(~0u, u[15], 1);
        u[17] = lane & 2 ? c[34] : c[32];
#pragma unroll
        for (int i = 0; i < 5; i++) {
          if (gap && i) __nanosleep(gap);
          red_add4(dst + i * 128, u[3 * i], u[3 * i + 1], u[3 * i + 2], i < 3 && !(lane & 1) ? u[i == 0 ? 15 : i == 1 ? 17 : 16] : 1.f);
        }
      };
      const uint32_t zero = lds32(sb + OFF_ONES) & 1;
      if (wg) reduce(kvacc, 0);
      const float l2e = __uint_as_float(lds32(sb + OFF_MISC + 20));
      uint32_t dep = 0;
#pragma unroll
      for (int u = 0; u < 8; u++) {
#pragma unroll
        for (int i = 0; i < 4; i++) dep |= pq[u >> 2][u & 3][i] = phi2(acc[u >> 2][8 * (u & 3) + 2 * i], acc[u >> 2][8 * (u & 3) + 2 * i + 1], l2e);
      }
      float4* const kvp = kvacc + (dep & zero);
      if (!wg) reduce(kvp, RED_SLEEP);
      PROF_C(wt == 0 && kvp == kvacc, 34 + wg * 2);
      for (int tries = wg ? 0 : 9;; tries++) {
        if (tries > RETRY)
          while (ld_relaxed((const unsigned*)&(kvp - lane)[NV * 128 - 128 + 31].w) != 0x41800000u) __nanosleep(wg ? KV_SLEEP : KV_SLEEP_A);
        float4 kv[NV];
#pragma unroll
        for (int i = 0; i < NV; i++) kv[i] = ld_relaxed_f4(kvp + i * 128);
        const uint32_t kb = sb + OFF_KVB + (w >> 1) * 2560 + (w & 1) * 256;
        const uint32_t ka = kb + (lane >> 4) * 512 + (lane & 15) * 16;
        stsm4(ka, pack2(kv[0].x, kv[0].y), pack2(kv[0].z, kv[1].x), pack2(kv[1].y, kv[1].z), pack2(kv[2].x, kv[2].y));
        const uint32_t zz = pack2(kv[1].w, kv[1].w);
        if (!(lane & 1)) sts128(kb + 2048 + (lane & 2) * 64 + (lane >> 2) * 16, zz, zz, zz, zz);
        const float u15 = __shfl_up_sync(~0u, kv[2].w, 1);
        stsm4(ka + 1024, pack2(kv[2].z, kv[3].x), pack2(kv[3].y, kv[3].z), pack2(kv[4].x, kv[4].y), pack2(kv[4].z, lane & 1 ? u15 : kv[0].w));
        const bool ok = !(lane & 1) || kv[0].w + kv[1].w + kv[2].w + kv[3].w + kv[4].w == 80.f;
        if (__all_sync(~0u, ok)) { PROF_V(wg && lane == 0, 40 + w, tries * 100 + 2); break; }
      }
    }
    {
      PROF_C(wt == 0, 5 + wg * 8);
      fence_async_smem();
      nb_sync(nb_self, 128);
      float o[2][2][20];
      const uint32_t dz = mkdesc(sb + OFF_KVB, 128);
      wg_fence();
#pragma unroll
      for (int m = 0; m < 2; m++) {
#pragma unroll
        for (int h = 0; h < 2; h++)
#pragma unroll
          for (int kk = 0; kk < 2; kk++) mma_qkvz(o[m][h], pq[m][2 * h + kk], dz + (h * 160 + kk * 16), kk);
        wg_commit();
      }
      const uint32_t tmask = (lane & 3) == (lane >> 3), tbit = lds32(sb + OFF_MISC + 24) & tmask;
      float gr[2][2], sc[4];
#pragma unroll
      for (int i = 0; i < 4; i++) gr[i >> 1][i & 1] = __uint_as_float(lds32(sb + OFF_G + ((i >> 1) * 64 + (i & 1) * 8 + w * 16 + (lane >> 2)) * 4));
      if (wg == 1) {
        mbar_arrive_warp(sb + BAR_OST);
        mbar_wait(sb + BAR_OA, 0);
      }
      const uint32_t os = sb + (wg ? OFF_MOD : OFF_PK) + w * 2048;
      uint8_t* const og = (uint8_t*)gs->o[tm][wg * 8 + tn] + w * 2048;
#pragma unroll
      for (int m = 0; m < 2; m++) {
        if (m == 0) wg_wait<1>();
        if (m == 0) PROF_C(wt == 0, 6 + wg * 8);
#pragma unroll
        for (int h = 0; h < 2; h++) {
          const float* oo = o[m][h];
          uint32_t pin = 0;
          if (!m && h) {
            wg_wait<0>();
#pragma unroll
            for (int i = 0; i < 4; i++) pin |= __float_as_uint(sc[i] = gr[1][i & 1] * rcp(o[1][i >> 1][16 + (i & 1) * 2] + 1e-6f));
            pin &= __float_as_uint(gr[0][0]) & 16;
          }
          const float s0 = m ? sc[2 * h] : gr[m][0] * rcp(oo[16] + 1e-6f), s1 = m ? sc[2 * h + 1] : gr[m][1] * rcp(oo[18] + 1e-6f);
#pragma unroll
          for (int j = 0; j < 2; j++)
            stsm4(os + m * 8192 + (lane & 15) * 128 + ((((lane >> 4) + 4 * h + 2 * j) ^ (lane & 7)) << 4) + (j ? pin : 0),
                  (pack2(oo[8 * j] * s0, oo[8 * j + 1] * s0) & ~tmask) | tbit, (pack2(oo[8 * j + 2] * s1, oo[8 * j + 3] * s1) & ~tmask) | tbit,
                  pack2(oo[8 * j + 4] * s0, oo[8 * j + 5] * s0), pack2(oo[8 * j + 6] * s1, oo[8 * j + 7] * s1));
        }
        fence_async_smem();
        __syncwarp();
        if (elect()) bulk_store(og + m * 8192, os + m * 8192, 2048);
      }
      if (elect()) {
        bulk_commit();
        if (wg) mbar_arrive(sb + BAR_OWN);
        PROF(wt == 0, 7 + wg * 8);
        if (!wg) red_add(gs->cnt[tm], 1u << tn * 4);
        asm volatile("cp.async.bulk.wait_group.read 0;" ::: "memory");
        PROF(wt == 0, 17 + wg);
        PROF(wt == 96, 38 + wg);
      }
    }

    __syncwarp();
    const uint32_t par = lds32(sb + OFF_MISC + 24), cw = lane * 32 + (lane & 4) * 4 + (lane >> 3) * 4;
    auto check_tile = [&](int g, uint32_t s) {
      const uint32_t a = sb + OFF_RING + s * O_BYTES + w * 2048, fix = sb + BAR_FIX + warp * 8;
      for (;;) {
        const uint32_t u0 = lds32(a + cw), u1 = lds32(a + cw + 1024), u2 = lds32(a + cw + 8192), u3 = lds32(a + cw + 9216);
        if (__all_sync(~0u, !(mism(mism(u0, u1, par), mism(u2, u3, par), 0) & 1))) break;
        PROF_V(lane == 0, 44 + g, 102);
        const int slab = g < OWN ? g : g < PEER ? g - 1 : g == PEER ? 8 + (tn ^ 1) : g - 10 < (tn & 6) ? g - 2 : g;
        const uint4* src = gs->o[tm][slab] + w * 128;
        const uint32_t ph = !mbar_test(fix, 1);
        fence_async_smem();
        __syncwarp();
        if (elect()) { mbar_expect_tx(fix, 4096); bulk_load(a, src, 2048, fix); bulk_load(a + 8192, src + 512, 2048, fix); }
        mbar_wait(fix, ph);
      }
    };
    if (wg == 1) {
#pragma unroll 1
      for (int g = 10; g < 16; g++) {
        const uint32_t s = g == 15 ? 0 : g - 10;
        mbar_wait(sb + BAR_LAND + (g - 10) * 8, 0);
        PROF_C(wt == 0, 214 + g);
        check_tile(g, s);
        if (w) nb_arrive(NB_CHK + (g & 1), 128);
        else { nb_sync(NB_CHK + (g & 1), 128); mbar_arrive_warp(sb + BAR_FULL + s * 8); }
        if (g & 1) nb_sync(nb_self, 128);
      }
    } else {
      nb_arrive(NB_STG, 256);
      float acc[2][64];
      mbar_wait(sb + BAR_W31, 0);
#pragma unroll 1
      for (int g = 0; g < PC; g++) { mbar_wait(sb + BAR_EMPTY + g * 8, 1); mbar_wait(sb + BAR_FULL + g * 8, 0); check_tile(g, g); }
      const uint32_t chk = __shfl_sync(~0u, lds32(sb + OFF_MISC + 28), 0);
      nb_sync(NB_ORDER_BO, 256);
      PROF_C(wt == 0, 26);
      uint32_t xr[2][8][4], q[2][2];
      const uint32_t ta = sb + OFF_PK + (uint32_t)(w * 16 + (lane & 15)) * 128;
#pragma unroll 1
      for (int g = 0; g < 13 - TL; g++) {
        const uint32_t r = g * 52 >> 8, s = g - r * 5;
        const uint32_t da = da0 + (g == OWN ? 5 : s) * (O_BYTES >> 4), db = db0 + s * (O_BYTES >> 4);
        if (g == OWN) {
          wg_wait<0>();
          mbar_arrive_warp(sb + BAR_EMPTY + (OWN + 4) % 5 * 8);
          mbar_wait(sb + BAR_OWN, 0);
        }
        mbar_wait(sb + BAR_FULL + s * 8, r & 1);
        if (chk >> g & 1) check_tile(g, s);
        PROF_C(wt == 0, 96 + g);
        wg_fence();
#pragma unroll
        for (int kk = 0; kk < 4; kk++)
#pragma unroll
          for (int m = 0; m < 2; m++) mma_out(acc[m], da + (m * 512 + kk * 2), db + kk * 128, kk ? 1 : g);
        wg_commit();
        wg_wait<1>();
        if (~(1 | 1 << OWN) >> g & 1) mbar_arrive_warp(sb + BAR_EMPTY + (s ? s - 1 : 4) * 8);
      }
      mbar_wait(sb + BAR_X, 0);
      if (((0xFFFF - (lds32(sb + OFF_MISC + 16) & 0xFFFF)) >> 7) == tm) mbar_wait(sb + BAR_Y, 0);
#pragma unroll
      for (int u = 0; u < 4; u++) {
        const int m = u >> 1, g = 13 - TL + u;
        const float g1 = 1.f - __uint_as_float(lds32(sb + OFF_G + (m * 64 + w * 16 + (u & 1) * 8 + (lane >> 2)) * 4));
        q[m][u & 1] = pack2(g1, g1);
#pragma unroll
        for (int j = 0; j < 4; j++) ldsm4(ta + (u & 1) * 16384 + m * 8192 + ((((lane >> 4) + 2 * j) ^ (lane & 7)) << 4), xr[m][(u & 1) * 4 + j]);
        if (u == 3) break;
        mbar_wait(sb + BAR_FULL + g % 5 * 8, g / 5 & 1);
        PROF_C(wt == 0, 96 + g);
        wg_fence();
#pragma unroll
        for (int kk = 0; kk < 4; kk++)
#pragma unroll
          for (int mm = 0; mm < 2; mm++)
            mma_out(acc[mm], da0 + (g % 5 * (O_BYTES >> 4) + mm * 512 + kk * 2), db0 + (g % 5 * (O_BYTES >> 4) + kk * 128), 1);
        wg_commit();
        wg_wait<1>();
        if (g <= 11) mbar_arrive_warp(sb + BAR_EMPTY + (g + 4) % 5 * 8);
      }
      auto half_step = [&](int m, int g) {
        if (m == 0) { mbar_wait(sb + BAR_FULL + g % 5 * 8, g / 5 & 1); PROF_C(wt == 0, 96 + g); wg_fence(); }
#pragma unroll
        for (int kk = 0; kk < 4; kk++)
          mma_out(acc[m], da0 + (g % 5 * (O_BYTES >> 4) + m * 512 + kk * 2), db0 + (g % 5 * (O_BYTES >> 4) + kk * 128), 1);
      };
      auto stage = [&](int m, int j0, int j1) {
#pragma unroll
        for (int j = j0; j < j1; j++) {
          const float* v = &acc[m][8 * j];
          stsm4(ta + (j >> 2) * 16384 + m * 8192 + ((((lane >> 4) + 2 * (j & 3)) ^ (lane & 7)) << 4),
                fma_bf2(xr[m][j][0], q[m][0], pack2(v[0], v[1])), fma_bf2(xr[m][j][1], q[m][1], pack2(v[2], v[3])),
                fma_bf2(xr[m][j][2], q[m][0], pack2(v[4], v[5])), fma_bf2(xr[m][j][3], q[m][1], pack2(v[6], v[7])));
        }
      };
      auto leave_tma = [&](int m, int h) {
        fence_async_smem();
        __syncwarp();
        if (elect()) tma2d_store(&p.out, sb + OFF_PK + h * 16384 + m * 8192 + w * 2048, tn * 128 + h * 64, tm * 128 + m * 64 + w * 16);
      };
      auto leave = [&](int m, int h) {
        __syncwarp();
        const uint32_t r = lane >> 3;
        uint4 v[4];
#pragma unroll
        for (int i = 0; i < 4; i++) v[i] = lds128(sb + OFF_PK + h * 16384 + m * 8192 + w * 2048 + (r + 4 * i) * 128 + (((lane ^ (r + 4 * i)) & 7) << 4));
        char* const dst = (char*)pout + (size_t)(tm * 128 + m * 64 + w * 16 + r) * (D_ * 2) + tn * 256 + h * 128 + (lane & 7) * 16;
#pragma unroll
        for (int i = 0; i < 4; i++) asm volatile("st.global.v4.u32 [%0], {%1, %2, %3, %4};" ::"l"(dst + i * 4 * D_ * 2), "r"(v[i].x), "r"(v[i].y), "r"(v[i].z), "r"(v[i].w) : "memory");
      };
#pragma unroll
      for (int g = 16 - TL; g < 16; g++) half_step(0, g);
      wg_commit();
#pragma unroll
      for (int g = 16 - TL; g < 16; g++) half_step(1, g);
      wg_commit();
      mbar_arrive_warp(sb + BAR_DONE);
      wg_wait<1>();
      PROF(wt == 0, 35);
      stage(0, 0, 4);
      leave_tma(0, 0);
      stage(0, 4, 8);
      leave_tma(0, 1);
      if (elect()) bulk_commit();
      PROF(wt == 0, 33);
      wg_wait<0>();
      PROF(wt == 0, 31);
#pragma unroll
      for (int h = 0; h < 2; h++) { stage(1, 4 * h, 4 * h + 4); leave(1, h); }
      if (elect()) asm volatile("cp.async.bulk.wait_group.read 0;" ::: "memory");
      PROF(wt == 0, 32);
    }
  }
}

typedef CUresult (*EncodeFn)(CUtensorMap*, CUtensorMapDataType, cuuint32_t, void*, const cuuint64_t*, const cuuint64_t*, const cuuint32_t*,
                             const cuuint32_t*, CUtensorMapInterleave, CUtensorMapSwizzle, CUtensorMapL2promotion, CUtensorMapFloatOOBfill);

void encode(EncodeFn fn, CUtensorMap* m, const void* ptr, int rank, const cuuint64_t* dims, const cuuint64_t* strides, const cuuint32_t* box,
            CUtensorMapSwizzle sw, CUtensorMapDataType dt = CU_TENSOR_MAP_DATA_TYPE_BFLOAT16) {
  const cuuint32_t es[3] = {1, 1, 1};
  fn(m, dt, rank, const_cast<void*>(ptr), dims, strides, box, es, CU_TENSOR_MAP_INTERLEAVE_NONE, sw,
     CU_TENSOR_MAP_L2_PROMOTION_L2_128B, CU_TENSOR_MAP_FLOAT_OOB_FILL_NONE);
}

}

extern "C" void kernel_launch(void* const* d_in, const int* in_sizes, int n_in, void* d_out, int out_size) {
  (void)in_sizes; (void)n_in; (void)out_size;
  EncodeFn fn = nullptr;
  cudaDriverEntryPointQueryResult qr;
  cudaGetDriverEntryPoint("cuTensorMapEncodeTiled", (void**)&fn, cudaEnableDefault, &qr);

  Params p;
  {
    const cuuint64_t dims[2] = {D_, S_}, str[1] = {D_ * 2};
    const cuuint32_t box[2] = {64, 128}, box_st[2] = {64, 16}, box_r[2] = {256, 16};
    encode(fn, &p.xr, d_in[0], 2, dims, str, box_r, CU_TENSOR_MAP_SWIZZLE_NONE);
    encode(fn, &p.x, d_in[0], 2, dims, str, box, CU_TENSOR_MAP_SWIZZLE_128B);
    encode(fn, &p.out, d_out, 2, dims, str, box_st, CU_TENSOR_MAP_SWIZZLE_128B);
  }
  {
    const cuuint64_t dims[3] = {D_, D_, 3}, str[2] = {3 * D_ * 2, D_ * 2};
    const cuuint32_t box[3] = {64, 64, 3};
    encode(fn, &p.w, d_in[1], 3, dims, str, box, CU_TENSOR_MAP_SWIZZLE_128B);
  }
  {
    const cuuint64_t dims[3] = {64, D_, D_ / 64}, str[2] = {D_ * 2, 128};
    const cuuint32_t box[3] = {64, 64, 2};
    encode(fn, &p.wo, d_in[2], 3, dims, str, box, CU_TENSOR_MAP_SWIZZLE_128B);
  }
  {
    const cuuint64_t dims[3] = {F_, D_ / 4, 4}, str[2] = {F_ * 8, F_ * 2};
    const cuuint32_t box[3] = {32, 16, 4};
    encode(fn, &p.gate, d_in[5], 3, dims, str, box, CU_TENSOR_MAP_SWIZZLE_NONE);
    encode(fn, &p.up, d_in[6], 3, dims, str, box, CU_TENSOR_MAP_SWIZZLE_NONE);
  }
  {
    const cuuint64_t dims[3] = {D_ / 4, F_, 2}, str[2] = {D_ * 2, D_};
    const cuuint32_t box[3] = {256, 4, 2};
    encode(fn, &p.down, d_in[7], 3, dims, str, box, CU_TENSOR_MAP_SWIZZLE_NONE, CU_TENSOR_MAP_DATA_TYPE_UINT32);
  }
  void* gs = nullptr;
  cudaGetSymbolAddress(&gs, g_scratch);
  typedef const __nv_bfloat16* bp;
  int dev = 0, sms = 0;
  cudaGetDevice(&dev);
  cudaDeviceGetAttribute(&sms, cudaDevAttrMultiProcessorCount, dev);
  const bool by_sm = BYSM && sms == NGRID;
  const auto kernel = by_sm ? fused_kernel<true> : fused_kernel<false>;
  cudaFuncSetAttribute(kernel, cudaFuncAttributeMaxDynamicSharedMemorySize, SMEM_BYTES);
  kernel<<<by_sm ? NGRID : NCTA, NTHREADS, SMEM_BYTES, cudaStreamPerThread>>>((bp)d_in[0], (Scratch*)gs, d_out, (bp)d_in[4], (bp)d_in[8], (bp)d_in[5], p, (bp)d_in[6]);
}
```

```cpp
#include <cuda_runtime.h>
#include <cuda.h>
#include <cuda_bf16.h>
#include <stdint.h>
#include <stddef.h>

namespace {

constexpr int S_ = 2048, D_ = 1024, F_ = 3584;
constexpr int NCTA = 128, NGRID = 132, NTHREADS = 512;
constexpr int MOD_CTAS = F_ / 32;

#define PC 2
#define PRE 2
#define ST1 700
#define RT_G0 2
#define RT_ORD 0x1032
#define RT_SLEEP 500
#define PF_MOD 6
#define MOD_START 9
#define MM 4
#define PA 6
#define RED_SLEEP 32
#define RETRY 1
#define KV_SLEEP_A 128
#define KV_SLEEP 50
#define OWN 5
#define TL 3
#define NOMOD 6
#define FSL 256
#define GMK 0x96
#define XG 0x4432
#define M1 1
#define PAIRED 1
#define BYSM 1

constexpr uint32_t A_BYTES = 16384, BQ_BYTES = 24576, BO_BYTES = 16384, STAGE_BYTES = A_BYTES + BQ_BYTES, O_BYTES = A_BYTES + BO_BYTES;
constexpr int MOD_BUFS = 3, MOD_BUFS0 = MOD_BUFS + 1;
static_assert(MOD_START + MOD_BUFS0 <= 16, "first FFN round is requested during wave A");
constexpr uint32_t OFF_RING = 0;
constexpr uint32_t OFF_MOD = 4 * STAGE_BYTES;
constexpr uint32_t OFF_PK = OFF_MOD + MOD_BUFS * 8192;
constexpr uint32_t OFF_V = OFF_PK + 16384;
constexpr uint32_t OFF_ONES = OFF_V + 16384;
constexpr uint32_t OFF_KVB = OFF_ONES + 2048;
constexpr uint32_t OFF_XSEL = OFF_KVB + 5120;
constexpr uint32_t OFF_G = OFF_XSEL + 2048;
constexpr uint32_t OFF_PART = OFF_G + 512;
constexpr uint32_t OFF_MISC = OFF_PART + 576;
constexpr uint32_t OFF_BAR = OFF_MISC + 32;
constexpr uint32_t BAR_FULL = OFF_BAR, BAR_EMPTY = OFF_BAR + 40, BAR_RTD = OFF_BAR + 80, BAR_Y = OFF_BAR + 88, BAR_DONE = OFF_BAR + 96,
                   BAR_X = OFF_BAR + 104, BAR_OA = OFF_BAR + 112, BAR_OWN = OFF_BAR + 120, BAR_OST = OFF_BAR + 128, BAR_PA = OFF_BAR + 136,
                   BAR_W31 = OFF_BAR + 144, BAR_MFULL = OFF_BAR + 152, BAR_MEMPTY = BAR_MFULL + MOD_BUFS0 * 8,
                   BAR_IDX = BAR_MEMPTY + MOD_BUFS * 8;
constexpr uint32_t SMEM_BYTES = OFF_BAR + 384;
static_assert(SMEM_BYTES <= 232448, "smem");

constexpr uint32_t BAR_LAND = OFF_BAR + 256, BAR_FIX = BAR_LAND + 64;
constexpr uint32_t BAR_RT = BAR_FIX;
static_assert(TL == 3 && PRE == 2 && BAR_IDX - OFF_BAR < 256, "warp w initialises barriers 2w and 2w + 1");
constexpr __host__ __device__ uint64_t bar_counts(int first) {
  uint64_t r = 0;
  for (uint32_t i = 0; i < 16; i++) {
    const uint32_t b = OFF_BAR + (first + i) * 8;
    const uint64_t c = b < BAR_EMPTY ? 2 : b == BAR_IDX ? 5 : b == BAR_Y || b == BAR_X || (b >= BAR_PA && b < BAR_MEMPTY) ? 1 : 4;
    r |= c << i * 4;
  }
  return r;
}

constexpr int NB_WG0 = 1, NB_ORDER_AB = 3, NB_ORDER_BO = 4, NB_STG = 5, NB_MODW = 6, NB_KEY = 7, NB_CHK = 8;

constexpr int NV = 5, NCLR = NV * 4 + 5;
struct Scratch {
  float4 kv[2][8][NV][128];
  float y[8][D_];
  unsigned cnt[64][32];
  unsigned gslot[S_];
  unsigned rslot[8][NCTA];
  unsigned spare[128];
  unsigned block[NCTA];
  uint4 o[16][16][1024];
};
static_assert(offsetof(Scratch, gslot) == NCTA * NCLR * 64, "clear size");
__device__ __align__(1024) Scratch g_scratch;

#define PROF(cond, i) do {} while (0)
#define PROF_C(cond, i) do {} while (0)
#define PROF_P(cond, i) do {} while (0)
#define PROF_V(cond, i, v) do {} while (0)

__device__ __forceinline__ void mbar_init(uint32_t bar, int cnt) { asm volatile("mbarrier.init.shared::cta.b64 [%0], %1;" ::"r"(bar), "r"(cnt)); }
__device__ __forceinline__ void mbar_expect_tx(uint32_t bar, uint32_t bytes) { asm volatile("mbarrier.arrive.expect_tx.shared::cta.b64 _, [%0], %1;" ::"r"(bar), "r"(bytes) : "memory"); }
__device__ __forceinline__ void mbar_arrive(uint32_t bar) { asm volatile("mbarrier.arrive.shared::cta.b64 _, [%0];" ::"r"(bar) : "memory"); }
__device__ __forceinline__ uint32_t peer_addr(uint32_t a) {
  uint32_t r;
  asm volatile("{\n.reg .u32 c;\nmov.u32 c, %%cluster_ctarank;\nxor.b32 c, c, 1;\nmapa.shared::cluster.u32 %0, %1, c;\n}" : "=r"(r) : "r"(a));
  return r;
}
__device__ __forceinline__ void mbar_arrive_peer(uint32_t bar) { asm volatile("mbarrier.arrive.shared::cluster.b64 _, [%0];" ::"r"(bar) : "memory"); }
__device__ __forceinline__ uint32_t mism(uint32_t a, uint32_t b, uint32_t p) {
  uint32_t r; asm("lop3.b32 %0, %1, %2, %3, 0x7E;" : "=r"(r) : "r"(a), "r"(b), "r"(p)); return r;
}
__device__ __forceinline__ bool elect() {
  uint32_t r;
  asm volatile("{\n.reg .pred p;\nelect.sync _|p, 0xffffffff;\nselp.u32 %0, 1, 0, p;\n}" : "=r"(r));
  return r;
}
__device__ __forceinline__ uint32_t fresh_tid() { uint32_t r; asm volatile("mov.u32 %0, %%tid.x;" : "=r"(r)); return r; }
__device__ __forceinline__ void mbar_arrive_warp(uint32_t bar) {
  asm volatile("{\n.reg .pred p;\nelect.sync _|p, 0xffffffff;\n@p mbarrier.arrive.shared::cta.b64 _, [%0];\n}" ::"r"(bar) : "memory");
}
__device__ __forceinline__ void mbar_wait(uint32_t bar, uint32_t parity) {
  asm volatile("{\n.reg .pred p;\nWAIT_L:\nmbarrier.try_wait.parity.shared::cta.b64 p, [%0], %1;\n@p bra DONE_L;\nbra WAIT_L;\nDONE_L:\n}"
               ::"r"(bar), "r"(parity) : "memory");
}
__device__ __forceinline__ uint32_t mbar_test(uint32_t bar, uint32_t parity) {
  uint32_t ok;
  asm volatile("{\n.reg .pred p;\nmbarrier.test_wait.parity.shared::cta.b64 p, [%1], %2;\nselp.u32 %0, 1, 0, p;\n}" : "=r"(ok) : "r"(bar), "r"(parity) : "memory");
  return ok;
}
constexpr unsigned long long WATCHDOG_NS = 2000000000ull;
__device__ __forceinline__ unsigned long long gtime() { unsigned long long t; asm volatile("mov.u64 %0, %%globaltimer;" : "=l"(t)); return t; }
__device__ __forceinline__ uint32_t clock32() { uint32_t t; asm volatile("mov.u32 %0, %%clock;" : "=r"(t)); return t; }
__device__ __forceinline__ void mbar_wait_bounded(uint32_t bar, uint32_t parity) {
  unsigned long long t0 = 0;
  for (;;) {
    uint32_t ok;
    asm volatile("{\n.reg .pred p;\nmbarrier.try_wait.parity.shared::cta.b64 p, [%1], %2;\nselp.u32 %0, 1, 0, p;\n}" : "=r"(ok) : "r"(bar), "r"(parity) : "memory");
    if (ok) break;
    const unsigned long long t1 = gtime();
    if (t0 == 0) t0 = t1;
    if (t1 - t0 > WATCHDOG_NS) __trap();
  }
}
__device__ __forceinline__ void tma2d(uint32_t dst, const CUtensorMap* m, int c0, int c1, uint32_t bar) {
  asm volatile("cp.async.bulk.tensor.2d.shared::cluster.global.mbarrier::complete_tx::bytes [%0], [%1, {%3, %4}], [%2];"
               ::"r"(dst), "l"(m), "r"(bar), "r"(c0), "r"(c1) : "memory");
}
__device__ __forceinline__ void tma3d(uint32_t dst, const CUtensorMap* m, int c0, int c1, int c2, uint32_t bar) {
  asm volatile("cp.async.bulk.tensor.3d.shared::cluster.global.mbarrier::complete_tx::bytes [%0], [%1, {%3, %4, %5}], [%2];"
               ::"r"(dst), "l"(m), "r"(bar), "r"(c0), "r"(c1), "r"(c2) : "memory");
}
__device__ __forceinline__ void tma3d_stream(uint32_t dst, const CUtensorMap* m, int c0, int c1, int c2, uint32_t bar) {
  asm volatile("cp.async.bulk.tensor.3d.shared::cluster.global.mbarrier::complete_tx::bytes.L2::cache_hint [%0], [%1, {%3, %4, %5}], [%2], %6;"
               ::"r"(dst), "l"(m), "r"(bar), "r"(c0), "r"(c1), "r"(c2), "l"(0x12F0000000000000ull) : "memory");
}
__device__ __forceinline__ void bulk_load(uint32_t dst, const void* src, uint32_t bytes, uint32_t bar) {
  asm volatile("cp.async.bulk.shared::cluster.global.mbarrier::complete_tx::bytes [%0], [%1], %2, [%3];" ::"r"(dst), "l"(src), "r"(bytes), "r"(bar) : "memory");
}
__device__ __forceinline__ void bulk_store(void* dst, uint32_t src, uint32_t bytes) {
  asm volatile("cp.async.bulk.global.shared::cta.bulk_group [%0], [%1], %2;" ::"l"(dst), "r"(src), "r"(bytes) : "memory");
}
__device__ __forceinline__ void bulk_push(uint32_t dst, uint32_t src, uint32_t bytes, uint32_t bar) {
  asm volatile("cp.async.bulk.shared::cluster.shared::cta.mbarrier::complete_tx::bytes [%0], [%1], %2, [%3];" ::"r"(dst), "r"(src), "r"(bytes), "r"(bar) : "memory");
}
__device__ __forceinline__ void bulk_commit() { asm volatile("cp.async.bulk.commit_group;" ::: "memory"); }
__device__ __forceinline__ void bulk_prefetch(const void* p, uint32_t bytes) {
  asm volatile("cp.async.bulk.prefetch.L2.global [%0], %1;" ::"l"(p), "r"(bytes) : "memory");
}
__device__ __forceinline__ void tma2d_store(const CUtensorMap* m, uint32_t src, int c0, int c1) {
  asm volatile("cp.async.bulk.tensor.2d.global.shared::cta.bulk_group [%0, {%2, %3}], [%1];" ::"l"(m), "r"(src), "r"(c0), "r"(c1) : "memory");
}
__device__ __forceinline__ void wg_fence() { asm volatile("wgmma.fence.sync.aligned;" ::: "memory"); }
__device__ __forceinline__ void wg_commit() { asm volatile("wgmma.commit_group.sync.aligned;" ::: "memory"); }
template <int N> __device__ __forceinline__ void wg_wait() { asm volatile("wgmma.wait_group.sync.aligned %0;" ::"n"(N) : "memory"); }
__device__ __forceinline__ void fence_async_smem() { asm volatile("fence.proxy.async.shared::cta;" ::: "memory"); }
__device__ __forceinline__ void fence_release() { asm volatile("fence.release.gpu;" ::: "memory"); }
__device__ __forceinline__ void fence_acquire() { asm volatile("fence.acquire.gpu;" ::: "memory"); }
__device__ __forceinline__ void nb_sync(int id, int n) { asm volatile("bar.sync %0, %1;" ::"r"(id), "r"(n) : "memory"); }
__device__ __forceinline__ void nb_arrive(int id, int n) { asm volatile("bar.arrive %0, %1;" ::"r"(id), "r"(n) : "memory"); }
__device__ __forceinline__ void stsm4(uint32_t addr, uint32_t r0, uint32_t r1, uint32_t r2, uint32_t r3) {
  asm volatile("stmatrix.sync.aligned.m8n8.x4.shared.b16 [%0], {%1, %2, %3, %4};" ::"r"(addr), "r"(r0), "r"(r1), "r"(r2), "r"(r3) : "memory");
}
__device__ __forceinline__ void sts128(uint32_t addr, uint32_t a, uint32_t b, uint32_t c, uint32_t d) {
  asm volatile("st.shared.v4.b32 [%0], {%1, %2, %3, %4};" ::"r"(addr), "r"(a), "r"(b), "r"(c), "r"(d) : "memory");
}
__device__ __forceinline__ uint32_t pack2(float lo, float hi) {
  uint32_t r; asm("cvt.rn.bf16x2.f32 %0, %1, %2;" : "=r"(r) : "f"(hi), "f"(lo)); return r;
}
__device__ __forceinline__ float bf_lo(uint32_t v) { return __uint_as_float(v << 16); }
__device__ __forceinline__ float bf_hi(uint32_t v) { return __uint_as_float(v & 0xffff0000u); }
__device__ __forceinline__ float bf_round(float v) { return __bfloat162float(__float2bfloat16_rn(v)); }
__device__ __forceinline__ void ldsm4(uint32_t addr, uint32_t (&r)[4]) {
  asm volatile("ldmatrix.sync.aligned.m8n8.x4.shared.b16 {%0, %1, %2, %3}, [%4];" : "=r"(r[0]), "=r"(r[1]), "=r"(r[2]), "=r"(r[3]) : "r"(addr) : "memory");
}
__device__ __forceinline__ uint4 lds128(uint32_t addr) {
  uint4 v; asm volatile("ld.volatile.shared.v4.u32 {%0, %1, %2, %3}, [%4];" : "=r"(v.x), "=r"(v.y), "=r"(v.z), "=r"(v.w) : "r"(addr) : "memory"); return v;
}
__device__ __forceinline__ uint2 lds64(uint32_t addr) { uint2 v; asm volatile("ld.volatile.shared.v2.u32 {%0, %1}, [%2];" : "=r"(v.x), "=r"(v.y) : "r"(addr) : "memory"); return v; }
__device__ __forceinline__ uint32_t lds32(uint32_t addr) { uint32_t v; asm volatile("ld.volatile.shared.u32 %0, [%1];" : "=r"(v) : "r"(addr) : "memory"); return v; }
__device__ __forceinline__ void sts32(uint32_t addr, uint32_t v) { asm volatile("st.shared.u32 [%0], %1;" ::"r"(addr), "r"(v) : "memory"); }
__device__ __forceinline__ uint32_t fma_bf2(uint32_t a, uint32_t b, uint32_t c) { uint32_t r; asm("fma.rn.bf16x2 %0, %1, %2, %3;" : "=r"(r) : "r"(a), "r"(b), "r"(c)); return r; }
__device__ __forceinline__ unsigned ld_relaxed(const unsigned* p) { unsigned v; asm volatile("ld.relaxed.gpu.global.u32 %0, [%1];" : "=r"(v) : "l"(p) : "memory"); return v; }
__device__ __forceinline__ void st_relaxed(unsigned* p, unsigned v) { asm volatile("st.relaxed.gpu.global.u32 [%0], %1;" ::"l"(p), "r"(v) : "memory"); }
__device__ __forceinline__ uint4 ld_relaxed4(const void* p) {
  uint4 v; asm volatile("ld.relaxed.gpu.global.v4.u32 {%0, %1, %2, %3}, [%4];" : "=r"(v.x), "=r"(v.y), "=r"(v.z), "=r"(v.w) : "l"(p) : "memory"); return v;
}
__device__ __forceinline__ float4 ld_relaxed_f4(const void* p) {
  float4 v; asm volatile("ld.relaxed.gpu.global.v4.f32 {%0, %1, %2, %3}, [%4];" : "=f"(v.x), "=f"(v.y), "=f"(v.z), "=f"(v.w) : "l"(p) : "memory"); return v;
}
__device__ __forceinline__ void red_add4(void* p, float a, float b, float c, float d) {
  asm volatile("red.relaxed.gpu.global.add.v4.f32 [%0], {%1, %2, %3, %4};" ::"l"(p), "f"(a), "f"(b), "f"(c), "f"(d) : "memory");
}
__device__ __forceinline__ void red_add(unsigned* p, unsigned v) { asm volatile("red.relaxed.gpu.global.add.u32 [%0], %1;" ::"l"(p), "r"(v) : "memory"); }
__device__ __forceinline__ void wait_counter(const unsigned* p, unsigned target) {
  while (ld_relaxed(p) < target) __nanosleep(32);
  fence_acquire();
}
__device__ __forceinline__ float rcp(float v) { float r; asm("rcp.approx.ftz.f32 %0, %1;" : "=f"(r) : "f"(v)); return r; }
__device__ __forceinline__ float sigmoidf_(float v) { return rcp(1.f + __expf(-v)); }
__device__ __forceinline__ uint32_t phi2(float a, float b, float l2e = 1.4426950408889634f) {
  float ea, eb;
  asm("ex2.approx.ftz.f32 %0, %1;" : "=f"(ea) : "f"(a * l2e));
  asm("ex2.approx.ftz.f32 %0, %1;" : "=f"(eb) : "f"(b * l2e));
  uint32_t t = pack2(a, b), e = pack2(ea, eb), r;
  asm("max.NaN.bf16x2 %0, %0, %1;" : "+r"(t) : "r"(0x35863586u));
  asm("min.bf16x2 %0, %0, %1;" : "+r"(e) : "r"(0x3F803F80u));
  asm("add.rn.bf16x2 %0, %1, %2;" : "=r"(r) : "r"(t), "r"(e));
  return r;
}
__device__ __forceinline__ uint32_t mkdesc(uint32_t addr, uint32_t lbo) { return ((addr & 0x3FFFF) >> 4) | ((lbo >> 4) << 16); }

__device__ __forceinline__ void mma_qkv(float (&d)[96], uint32_t da, uint32_t db, int sc) {
  asm volatile("{\n.reg .pred p;\n.reg .b64 da, db;\nmov.b64 da, {%96, 0x40000040};\nmov.b64 db, {%97, 0x40000040};\nsetp.ne.b32 p, %98, 0;\n"
    "wgmma.mma_async.sync.aligned.m64n192k16.f32.bf16.bf16 "
    "{%0,%1,%2,%3,%4,%5,%6,%7,%8,%9,%10,%11,%12,%13,%14,%15,%16,%17,%18,%19,%20,%21,%22,%23,"
    "%24,%25,%26,%27,%28,%29,%30,%31,%32,%33,%34,%35,%36,%37,%38,%39,%40,%41,%42,%43,%44,%45,%46,%47,"
    "%48,%49,%50,%51,%52,%53,%54,%55,%56,%57,%58,%59,%60,%61,%62,%63,%64,%65,%66,%67,%68,%69,%70,%71,"
    "%72,%73,%74,%75,%76,%77,%78,%79,%80,%81,%82,%83,%84,%85,%86,%87,%88,%89,%90,%91,%92,%93,%94,%95}, "
    "da, db, p, 1, 1, 0, 1;\n}\n"
    : "+f"(d[0]), "+f"(d[1]), "+f"(d[2]), "+f"(d[3]), "+f"(d[4]), "+f"(d[5]), "+f"(d[6]), "+f"(d[7]),
      "+f"(d[8]), "+f"(d[9]), "+f"(d[10]), "+f"(d[11]), "+f"(d[12]), "+f"(d[13]), "+f"(d[14]), "+f"(d[15]),
      "+f"(d[16]), "+f"(d[17]), "+f"(d[18]), "+f"(d[19]), "+f"(d[20]), "+f"(d[21]), "+f"(d[22]), "+f"(d[23]),
      "+f"(d[24]), "+f"(d[25]), "+f"(d[26]), "+f"(d[27]), "+f"(d[28]), "+f"(d[29]), "+f"(d[30]), "+f"(d[31]),
      "+f"(d[32]), "+f"(d[33]), "+f"(d[34]), "+f"(d[35]), "+f"(d[36]), "+f"(d[37]), "+f"(d[38]), "+f"(d[39]),
      "+f"(d[40]), "+f"(d[41]), "+f"(d[42]), "+f"(d[43]), "+f"(d[44]), "+f"(d[45]), "+f"(d[46]), "+f"(d[47]),
      "+f"(d[48]), "+f"(d[49]), "+f"(d[50]), "+f"(d[51]), "+f"(d[52]), "+f"(d[53]), "+f"(d[54]), "+f"(d[55]),
      "+f"(d[56]), "+f"(d[57]), "+f"(d[58]), "+f"(d[59]), "+f"(d[60]), "+f"(d[61]), "+f"(d[62]), "+f"(d[63]),
      "+f"(d[64]), "+f"(d[65]), "+f"(d[66]), "+f"(d[67]), "+f"(d[68]), "+f"(d[69]), "+f"(d[70]), "+f"(d[71]),
      "+f"(d[72]), "+f"(d[73]), "+f"(d[74]), "+f"(d[75]), "+f"(d[76]), "+f"(d[77]), "+f"(d[78]), "+f"(d[79]),
      "+f"(d[80]), "+f"(d[81]), "+f"(d[82]), "+f"(d[83]), "+f"(d[84]), "+f"(d[85]), "+f"(d[86]), "+f"(d[87]),
      "+f"(d[88]), "+f"(d[89]), "+f"(d[90]), "+f"(d[91]), "+f"(d[92]), "+f"(d[93]), "+f"(d[94]), "+f"(d[95])
    : "r"(da), "r"(db), "r"(sc));
}

__device__ __forceinline__ void mma_out(float (&d)[64], uint32_t da, uint32_t db, int sc) {
  asm volatile("{\n.reg .pred p;\n.reg .b64 da, db;\nmov.b64 da, {%64, 0x40000040};\nmov.b64 db, {%65, 0x40000040};\nsetp.ne.b32 p, %66, 0;\n"
    "wgmma.mma_async.sync.aligned.m64n128k16.f32.bf16.bf16 "
    "{%0,%1,%2,%3,%4,%5,%6,%7,%8,%9,%10,%11,%12,%13,%14,%15,%16,%17,%18,%19,%20,%21,%22,%23,"
    "%24,%25,%26,%27,%28,%29,%30,%31,%32,%33,%34,%35,%36,%37,%38,%39,%40,%41,%42,%43,%44,%45,%46,%47,"
    "%48,%49,%50,%51,%52,%53,%54,%55,%56,%57,%58,%59,%60,%61,%62,%63}, "
    "da, db, p, 1, 1, 0, 1;\n}\n"
    : "+f"(d[0]), "+f"(d[1]), "+f"(d[2]), "+f"(d[3]), "+f"(d[4]), "+f"(d[5]), "+f"(d[6]), "+f"(d[7]),
      "+f"(d[8]), "+f"(d[9]), "+f"(d[10]), "+f"(d[11]), "+f"(d[12]), "+f"(d[13]), "+f"(d[14]), "+f"(d[15]),
      "+f"(d[16]), "+f"(d[17]), "+f"(d[18]), "+f"(d[19]), "+f"(d[20]), "+f"(d[21]), "+f"(d[22]), "+f"(d[23]),
      "+f"(d[24]), "+f"(d[25]), "+f"(d[26]), "+f"(d[27]), "+f"(d[28]), "+f"(d[29]), "+f"(d[30]), "+f"(d[31]),
      "+f"(d[32]), "+f"(d[33]), "+f"(d[34]), "+f"(d[35]), "+f"(d[36]), "+f"(d[37]), "+f"(d[38]), "+f"(d[39]),
      "+f"(d[40]), "+f"(d[41]), "+f"(d[42]), "+f"(d[43]), "+f"(d[44]), "+f"(d[45]), "+f"(d[46]), "+f"(d[47]),
      "+f"(d[48]), "+f"(d[49]), "+f"(d[50]), "+f"(d[51]), "+f"(d[52]), "+f"(d[53]), "+f"(d[54]), "+f"(d[55]),
      "+f"(d[56]), "+f"(d[57]), "+f"(d[58]), "+f"(d[59]), "+f"(d[60]), "+f"(d[61]), "+f"(d[62]), "+f"(d[63])
    : "r"(da), "r"(db), "r"(sc));
}

__device__ __forceinline__ void mma_ktv(float (&d)[36], uint32_t da, uint32_t db, int sc) {
  asm volatile("{\n.reg .pred p;\n.reg .b64 da, db;\nmov.b64 da, {%36, 0x40000040};\nmov.b64 db, {%37, 0x40000040};\nsetp.ne.b32 p, %38, 0;\n"
    "wgmma.mma_async.sync.aligned.m64n72k16.f32.bf16.bf16 "
    "{%0,%1,%2,%3,%4,%5,%6,%7,%8,%9,%10,%11,%12,%13,%14,%15,%16,%17,%18,%19,%20,%21,%22,%23,"
    "%24,%25,%26,%27,%28,%29,%30,%31,%32,%33,%34,%35}, "
    "da, db, p, 1, 1, 1, 1;\n}\n"
    : "+f"(d[0]), "+f"(d[1]), "+f"(d[2]), "+f"(d[3]), "+f"(d[4]), "+f"(d[5]), "+f"(d[6]), "+f"(d[7]),
      "+f"(d[8]), "+f"(d[9]), "+f"(d[10]), "+f"(d[11]), "+f"(d[12]), "+f"(d[13]), "+f"(d[14]), "+f"(d[15]),
      "+f"(d[16]), "+f"(d[17]), "+f"(d[18]), "+f"(d[19]), "+f"(d[20]), "+f"(d[21]), "+f"(d[22]), "+f"(d[23]),
      "+f"(d[24]), "+f"(d[25]), "+f"(d[26]), "+f"(d[27]), "+f"(d[28]), "+f"(d[29]), "+f"(d[30]), "+f"(d[31]),
      "+f"(d[32]), "+f"(d[33]), "+f"(d[34]), "+f"(d[35])
    : "r"(da), "r"(db), "r"(sc));
}

__device__ __forceinline__ void mma_qkvz(float (&d)[20], const uint32_t (&a)[4], uint32_t db, int sc) {
  asm volatile("{\n.reg .pred p;\n.reg .b64 db;\nmov.b64 db, {%24, 0x20};\nsetp.ne.b32 p, %25, 0;\n"
    "wgmma.mma_async.sync.aligned.m64n40k16.f32.bf16.bf16 "
    "{%0,%1,%2,%3,%4,%5,%6,%7,%8,%9,%10,%11,%12,%13,%14,%15,%16,%17,%18,%19}, "
    "{%20,%21,%22,%23}, db, p, 1, 1, 1;\n}\n"
    : "+f"(d[0]), "+f"(d[1]), "+f"(d[2]), "+f"(d[3]), "+f"(d[4]), "+f"(d[5]), "+f"(d[6]), "+f"(d[7]),
      "+f"(d[8]), "+f"(d[9]), "+f"(d[10]), "+f"(d[11]), "+f"(d[12]), "+f"(d[13]), "+f"(d[14]), "+f"(d[15]),
      "+f"(d[16]), "+f"(d[17]), "+f"(d[18]), "+f"(d[19])
    : "r"(a[0]), "r"(a[1]), "r"(a[2]), "r"(a[3]), "r"(db), "r"(sc));
}

struct Params {
  CUtensorMap x, w, xr, wo, out, gate, up, down;
};

__device__ __forceinline__ void fma8(float (&acc)[8], const uint4& w, float m) {
  acc[0] = fmaf(bf_lo(w.x), m, acc[0]); acc[1] = fmaf(bf_hi(w.x), m, acc[1]);
  acc[2] = fmaf(bf_lo(w.y), m, acc[2]); acc[3] = fmaf(bf_hi(w.y), m, acc[3]);
  acc[4] = fmaf(bf_lo(w.z), m, acc[4]); acc[5] = fmaf(bf_hi(w.z), m, acc[5]);
  acc[6] = fmaf(bf_lo(w.w), m, acc[6]); acc[7] = fmaf(bf_hi(w.w), m, acc[7]);
}
__device__ __forceinline__ float butterfly8(float (&s)[8], int lane, int o) {
#pragma unroll
  for (int k = 1; k < 8; k <<= 1) {
    const bool up = lane & (o * k);
#pragma unroll
    for (int j = 0; j < 4 / k; j++) s[j] = (up ? s[2 * j + 1] : s[2 * j]) + __shfl_xor_sync(~0u, up ? s[2 * j] : s[2 * j + 1], o * k);
  }
  return s[0];
}
constexpr int PEER = 9;
constexpr __host__ __device__ uint32_t step_list() {
  uint32_t r = 0;
  for (int j = PEER - 1; j >= 0; j--) if (j != OWN) r = r << 4 | j % 5 | (j < 5) << 3;
  return r;
}
template <bool BY_SM> struct Tile {
  int sm, tm, tn, mu;
  bool spare;
  __device__ __forceinline__ Tile() {
    if (BY_SM) asm volatile("mov.u32 %0, %%smid;" : "=r"(sm));
    else sm = blockIdx.x + (blockIdx.x >= 120) * 4;
    const int tp = sm >> 1, pr = sm & 1;
    const int v = tp < 32 ? tp : tp < 60 ? (tp * 293 - 928) >> 8 : tp * 8 - 464, g = v & 7, i = v >> 3;
    const int j = i * 11 >> 5, c = i - j * 3;
    tm = (v & 6) * 2 + (c < 2 ? j : 3); tn = (GMK * 4 >> g & 4) + (c < 2 ? c : j) * 2 + pr;
    mu = i == NOMOD ? 112 : g * 14 + (i - (i > NOMOD)) * 2 + pr;
    spare = (tp | 1) == 61;
  }
};

template <bool BY_SM> __global__ void __cluster_dims__(2, 1, 1) __launch_bounds__(NTHREADS, 1)
fused_kernel(const __nv_bfloat16* __restrict__ px, Scratch* gs, void* pout, const __nv_bfloat16* __restrict__ w_r, const __nv_bfloat16* __restrict__ gate_w,
             const __nv_bfloat16* __restrict__ w_gate, const __grid_constant__ Params p, const __nv_bfloat16* __restrict__ w_up) {
  extern __shared__ __align__(1024) uint8_t smem[];
  const uint32_t sb = __shfl_sync(~0u, (uint32_t)__cvta_generic_to_shared(smem), 0);
  const int tid = threadIdx.x, lane = tid & 31;
  const int warp = __shfl_sync(~0u, tid >> 5, 0), wg = warp >> 2;
  const uint32_t t_start = clock32();
  const Tile<BY_SM> tile;
  const int tm = tile.tm, tn = tile.tn, mu = tile.mu, cta = tm * 8 + tn;
  {
    const uint32_t cnt = (uint32_t)((warp & 8 ? bar_counts(16) : bar_counts(0)) >> (warp & 7) * 8);
    if (elect()) mbar_init(sb + OFF_BAR + warp * 16, cnt & 15);
    if (elect()) mbar_init(sb + OFF_BAR + warp * 16 + 8, cnt >> 4 & 15);
    if (elect()) mbar_init(sb + BAR_LAND + warp * 8, 1);
    asm volatile("fence.mbarrier_init.release.cluster;" ::: "memory");
  }
  if (warp == 0 && !tile.spare) {
#pragma unroll
    for (int s = 0; s < PRE; s++) {
      if (elect()) tma3d(sb + OFF_RING + s * STAGE_BYTES + A_BYTES, &p.w, tn * 64, s * 64, 0, sb + BAR_FULL + s * 8);
      if (elect()) tma2d(sb + OFF_RING + s * STAGE_BYTES, &p.x, s * 64, tm * 128, sb + BAR_FULL + s * 8);
      PROF_P(lane == 0, 64 + s);
    }
    if (elect()) {
#pragma unroll
      for (int s = 0; s < PRE; s++) { mbar_expect_tx(sb + BAR_FULL + s * 8, STAGE_BYTES); mbar_arrive(sb + BAR_FULL + s * 8); }
    }
  }
  asm volatile("" ::: "memory");
  if (warp == 5) {
#pragma unroll
    for (int i = 0; i < 4; i++) sts128(sb + OFF_ONES + i * 512 + lane * 16, 0x3F803F80u, 0x3F803F80u, 0x3F803F80u, 0x3F803F80u);
    sts32(sb + OFF_MISC + 20, 0x3FB8AA3Bu);
    fence_async_smem();
  }
  __syncthreads();
  if (tile.spare) {
    if (warp == 0) {
      const unsigned tag = (ld_relaxed(&gs->spare[tile.sm & 3]) + 1) & 0xFFF;
      const unsigned long long t0 = gtime();
      uint4 r4;
      do {
        __nanosleep(2048);
        if (gtime() - t0 > WATCHDOG_NS) __trap();
        r4 = ld_relaxed4(&gs->rslot[tile.sm & 3][lane * 4]);
      } while (!__all_sync(~0u, (((r4.x ^ tag) | (r4.y ^ tag) | (r4.z ^ tag) | (r4.w ^ tag)) & 0xFFF) == 0));
      if (tid == 0) st_relaxed(&gs->spare[tile.sm & 3], tag);
    }
    return;
  }

  if (wg == 3) {
    asm volatile("setmaxnreg.dec.sync.aligned.u32 24;");
    if (warp == 12) {
      mbar_wait(sb + BAR_W31, 0);
      mbar_wait(sb + BAR_IDX, 0);
      const uint32_t lowb = (1u << (tn & 6) * 4) - 1;
      uint32_t slabs = 0x76543210u, steps = step_list();
      const uint4* src = gs->o[tm][0];
      unsigned seen = 0;
#pragma unroll 1
      for (int n = 8; n >= 6; n -= 2) {
#pragma unroll 1
        for (int i = 0; i < n; i++, slabs >>= 4, steps >>= 4) {
          const uint32_t s = steps & 7, full = sb + BAR_FULL + s * 8, need = 4u << (slabs & 7) * 4;
          const uint32_t land = n == 8 ? full : sb + BAR_LAND + i * 8;
          mbar_wait(full + (BAR_EMPTY - BAR_FULL), steps >> 3 & 1);
          PROF(lane == 0 && (!PROFC || n == 6), 224 + i + (n == 6) * 10);
          if (!__all_sync(~0u, seen & need)) {
            while (!__all_sync(~0u, (seen = ld_relaxed(gs->cnt[tm])) & need)) __nanosleep(FSL);
          }
          if (elect()) bulk_load(sb + OFF_RING + s * O_BYTES, src + (slabs & 7) * 1024, A_BYTES, land);
          if (elect()) mbar_expect_tx(land, A_BYTES);
          PROF(lane == 0 && (!PROFC || n == 6), 240 + i + (n == 6) * 10);
        }
        slabs = (0x76543210u & lowb) | (0x765432u & ~lowb);
        steps = 0x0CBA98u;
        src += 8 * 1024;
      }
    } else if (warp == 13) {
      uint32_t full = sb + BAR_FULL + PRE * 8, dst = sb + OFF_RING + PRE * STAGE_BYTES + A_BYTES, c0 = tn * 64, c1 = PRE * 64;
#pragma unroll 1
      for (int g = PRE; g < 32; g++) {
        if (g < 4) while ((int)(clock32() - t_start) < g * ST1) {}
        const bool reuse = (g >> 2) == 4;
        mbar_wait(full + (BAR_EMPTY - BAR_FULL), ((g >> 2) & 1) ^ 1);
        if (!reuse && elect()) tma2d(dst - A_BYTES, &p.x, c1, tm * 128, full);
        if (elect()) tma3d(dst, &p.w, c0, c1, 0, full);
        if (elect()) { mbar_expect_tx(full, reuse ? BQ_BYTES : STAGE_BYTES); mbar_arrive(full); }

        PROF_P(lane == 0, 64 + g);
        const uint32_t i = g - RT_G0;
        if (i < 4 && elect()) {
          mbar_expect_tx(sb + BAR_RT + i * 8, i ? 8192 : 8192 + 4096);
          tma2d(sb + OFF_PK + i * 8192, &p.xr, (RT_ORD >> i * 4 & 3) * 256, cta * 16, sb + BAR_RT + i * 8);
          if (i == 0) { bulk_load(sb + OFF_KVB, w_r, 2048, sb + BAR_RT); bulk_load(sb + OFF_KVB + 2048, gate_w, 2048, sb + BAR_RT); }
        }
        const uint32_t c = g - MOD_START;
        if (c == MOD_BUFS) mbar_wait(sb + BAR_RTD, 0);
        if (c < MOD_BUFS0 && mu < MOD_CTAS && elect()) {
          PROF_P(true, 192 + c);
          const uint32_t mfull = sb + BAR_MFULL + c * 8, mdst = sb + OFF_MOD + c * 8192;
          mbar_expect_tx(mfull, c ? 8192 : 8192 + 2048);
          tma3d(mdst, &p.gate, mu * 32, c * 16, 0, mfull); tma3d(mdst + 4096, &p.up, mu * 32, c * 16, 0, mfull);
        }
        const uint32_t pc = g - PF_MOD;
        if (pc < 16 && elect()) bulk_prefetch((cta & 64 ? w_up : w_gate) + (size_t)(pc * 64 + (cta & 63)) * F_, F_ * 2);
        full += 8; dst += STAGE_BYTES; c1 += 64;
        if ((g & 3) == 3) { full -= 32; dst -= 4 * STAGE_BYTES; }
        if (g == 15) { c0 += 512; c1 = 768; }
        if (g == 19) c1 = 0;
      }
      mbar_arrive_warp(sb + BAR_W31);
      const uint32_t lowb = (1u << (tn & 6) * 4) - 1;
      uint64_t slabs = (uint64_t)((0xFEDCBA98u & lowb) | (0xFEDCBAu & ~lowb)) << 40 | (uint64_t)(8 + (tn ^ 1)) << 36 | (uint64_t)(8 + tn) << OWN * 4 |
                       (0x76543210ull & ~(~0ull << OWN * 4)) | (0x765432100ull & ~0ull << (OWN * 4 + 4));
      uint32_t ph = 1;
      c1 = 0;
#pragma unroll 1
      for (int g = 0; g < 16; g++) {
        mbar_wait(full + (BAR_EMPTY - BAR_FULL), ph);
        if (elect()) tma3d(dst, &p.wo, 0, c1, tn * 2, full);
        if (elect()) mbar_expect_tx(full, BO_BYTES);
        PROF_P(lane == 0, 96 + g);
        if (g == OWN && elect()) mbar_arrive(full);
        full += 8; dst += O_BYTES; slabs >>= 4; c1 = ((uint32_t)slabs & 15) * 64;
        if (full == sb + BAR_EMPTY) { full -= 40; dst -= 5 * O_BYTES; ph ^= 1; }
      }
    } else if (warp == 14) {
      if (mu < MOD_CTAS) {
        uint32_t full = sb + BAR_MFULL, dst = sb + OFF_MOD, ph = 0;
#pragma unroll 1
        for (int c = MOD_BUFS0; c < 24; c++) {
          mbar_wait(full + (BAR_MEMPTY - BAR_MFULL), ph);
          PROF_P(lane == 0, 192 + c);
          if (c < 16) {
            if (elect()) { tma3d(dst, &p.gate, mu * 32, c * 16, 0, full); tma3d(dst + 4096, &p.up, mu * 32, c * 16, 0, full); }
          } else if (elect()) tma3d_stream(dst, &p.down, 0, mu * 32 + (c - 16) * 4, 0, full);
          if (elect()) mbar_expect_tx(full, 8192);
          full += 8; dst += 8192;
          if (dst == sb + OFF_PK) { full -= MOD_BUFS * 8; dst = sb + OFF_MOD; ph ^= 1; }
        }
      }
      if (elect()) {
      mbar_wait(sb + BAR_IDX, 0);
      const bool paired = lds32(sb + OFF_MISC + 28) < 0x200;
      const uint32_t pb = peer_addr(sb);
      mbar_wait(sb + BAR_EMPTY + PEER % 5 * 8, 0);
      mbar_expect_tx(sb + BAR_FULL + PEER % 5 * 8, A_BYTES);
      if (paired) mbar_arrive_peer(pb + BAR_PA);
      mbar_wait(sb + BAR_OST, 0);
      mbar_expect_tx(sb + BAR_X, 32768);
      tma2d(sb + OFF_PK, &p.x, tn * 128, tm * 128, sb + BAR_X);
      tma2d(sb + OFF_V, &p.x, tn * 128 + 64, tm * 128, sb + BAR_X);
      if (paired) {
        mbar_wait(sb + BAR_PA, 0);
        mbar_wait(sb + BAR_OWN, 0);
        bulk_push(pb + OFF_RING + PEER % 5 * O_BYTES, sb + OFF_MOD, A_BYTES, pb + BAR_FULL + PEER % 5 * 8);
        mbar_wait(sb + BAR_EMPTY + PEER % 5 * 8, 1);
        mbar_arrive_peer(pb + BAR_PA);
        mbar_wait(sb + BAR_PA, 1);
      } else {
        mbar_wait(sb + BAR_EMPTY + OWN % 5 * 8, 1);
        bulk_load(sb + OFF_RING + PEER % 5 * O_BYTES, gs->o[tm][8 + (tn ^ 1)], A_BYTES, sb + BAR_FULL + PEER % 5 * 8);
      }
      }
    } else if (elect()) {
#pragma unroll 1
      for (int i = 2; i < 8; i++) asm volatile("prefetch.tensormap [%0];" ::"l"(&p.x + i) : "memory");
      mbar_wait_bounded(sb + BAR_DONE, 0);
    }
  } else if (wg == 2) {
    asm volatile("setmaxnreg.dec.sync.aligned.u32 40;");
    const int mw = warp & 3;
    if (mw == 0) {
      const unsigned tag = (ld_relaxed(&gs->rslot[tn][cta]) + 1) & 0xFFF;
#pragma unroll
      for (int i = 0; i < 4; i++)
        if (lane < NCLR) ((float4*)gs)[cta * (NCLR * 4) + i * NCLR + lane] = make_float4(0.f, 0.f, 0.f, 0.f);
      if (lane == 29) st_relaxed(&gs->block[cta], blockIdx.x << 12 | tag);
      fence_release();
      nb_sync(NB_KEY, 160);
      const uint4 k4 = lds128(sb + OFF_MISC);
      if (lane < 8) st_relaxed(&gs->rslot[lane][cta], max(max(k4.x, k4.y), max(k4.z, k4.w)) | tag);
      if (lane < 16) st_relaxed(&gs->gslot[cta * 16 + lane], lds32(sb + OFF_G + lane * 4) | tag);
      PROF(lane == 0, 20);
      uint4 r4;
      do {
        __nanosleep(RT_SLEEP);
        r4 = ld_relaxed4(&gs->rslot[tn][lane * 4]);
      } while (!__all_sync(~0u, (((r4.x ^ tag) | (r4.y ^ tag) | (r4.z ^ tag) | (r4.w ^ tag)) & 0xFFF) == 0));
      const int c0 = 0xFFF0 - lane * 64;
      unsigned key = max(max((r4.x & 0xFFFF0000u) | (c0 + ((r4.x >> 12) & 15)), (r4.y & 0xFFFF0000u) | (c0 - 16 + ((r4.y >> 12) & 15))),
                         max((r4.z & 0xFFFF0000u) | (c0 - 32 + ((r4.z >> 12) & 15)), (r4.w & 0xFFFF0000u) | (c0 - 48 + ((r4.w >> 12) & 15))));
      key = __reduce_max_sync(~0u, key);
      if (elect()) {
        sts32(sb + OFF_MISC + 16, key);
        sts32(sb + OFF_MISC + 24, tag & 1);
        if (mu < MOD_CTAS) bulk_load(sb + OFF_XSEL, px + (size_t)(0xFFFF - (key & 0xFFFF)) * D_, 2048, sb + BAR_MFULL);
      }
      PROF(lane == 0, 21);
      unsigned nb;
      do {
        r4 = ld_relaxed4(&gs->gslot[tm * 128 + lane * 4]);
        nb = ld_relaxed(&gs->block[cta ^ 1]);
      } while (!__all_sync(~0u, (((r4.x ^ tag) | (r4.y ^ tag) | (r4.z ^ tag) | (r4.w ^ tag) | (nb ^ tag)) & 0xFFF) == 0));
      sts128(sb + OFF_G + lane * 16, r4.x & 0xFFFF0000u, r4.y & 0xFFFF0000u, r4.z & 0xFFFF0000u, r4.w & 0xFFFF0000u);
      sts32(sb + OFF_MISC + 28, (PAIRED && nb >> 12 == (blockIdx.x ^ 1) ? 0x1FF : 0x3FF) & ~((1 << PC) - 1 | 1 << OWN));
      fence_acquire();
      __syncwarp();
      mbar_arrive_warp(sb + BAR_IDX);
    }
    PROF(tid == 256, 22);
    if (mu >= MOD_CTAS) {
      mbar_arrive_warp(sb + BAR_IDX);
      mbar_arrive_warp(sb + BAR_OA);
    } else {
      const uint32_t wp = sb + OFF_MOD + (mw >> 1) * 4096 + (mw & 1) * 512 + lane * 16;
      uint32_t mp = sb + OFF_XSEL - 128 + (mw & 1) * 64 + (lane >> 2) * 8, mc = 128;
      float acc[8] = {0.f, 0.f, 0.f, 0.f, 0.f, 0.f, 0.f, 0.f};
      uint32_t b = ~0u, ph = 0, a = sb + OFF_ONES - 3072;
      float m3 = 0.f;
      const uint32_t zero = lds32(sb + OFF_ONES) & 1;
      uint2 m = make_uint2(0, 0);
      uint4 w0 = make_uint4(0, 0, 0, 0), w1 = w0, w2 = w0, w3 = w0;
#pragma unroll 1
      for (int c = -1;; c++) {
        fma8(acc, w3, m3);
        w3 = lds128(a + 3072);
        const uint32_t rel = sb + BAR_MEMPTY + b * 8;
        if (c == 16) {
          const uint32_t ft = fresh_tid(), fl = ft & 31;
          sts32(sb + OFF_PART + (ft & 96) * 4 + ((ft & 3) * 8 + (fl >> 2)) * 4, __float_as_uint(butterfly8(acc, fl, 4)));
          nb_sync(NB_MODW, 128);
          const float* part = (const float*)(smem + OFF_PART) + fl;
          const float gp = bf_round(part[0] + part[32]), up = bf_round(part[64] + part[96]);
          *(__nv_bfloat16*)(smem + OFF_PART + 512 + fl * 2) = __float2bfloat16_rn(bf_round(gp * sigmoidf_(gp)) * up);
          __syncwarp();
          mp = sb + OFF_PART + 512; mc = 8;
          m = lds64(mp);
#pragma unroll
          for (int i = 0; i < 8; i++) acc[i] = 0.f;
          PROF(lane == 0 && mw == 0, 23);
        }
        if (++b == (c < MOD_BUFS0 ? MOD_BUFS0 : MOD_BUFS)) { b = 0; ph ^= 1; }
        const uint32_t ok = mbar_test(sb + BAR_MFULL + b * 8, ph);
        fma8(acc, w0, bf_lo(m.x));
        if (c >= 0) mbar_arrive_warp(rel + ((w3.x | __float_as_uint(acc[7])) & zero));
        fma8(acc, w1, bf_hi(m.x));
        fma8(acc, w2, bf_lo(m.y));
        m3 = bf_hi(m.y);
        if (c == 23) break;
        if (!ok) mbar_wait(sb + BAR_MFULL + b * 8, ph);
        a = wp + b * 8192;
        mp += mc;
        m = lds64(mp);
        w0 = lds128(a); w1 = lds128(a + 1024); w2 = lds128(a + 2048);
      }
      fma8(acc, w3, m3);
      mbar_arrive_warp(sb + BAR_OA);
      float* yacc = gs->y[tn] + (fresh_tid() & 127) * 8;
      red_add4(yacc, acc[0], acc[1], acc[2], acc[3]);
      red_add4(yacc + 4, acc[4], acc[5], acc[6], acc[7]);
      PROF(lane == 0 && mw == 0, 25);
      nb_sync(NB_MODW, 128);
      if (mw == 0 && elect()) { fence_release(); red_add(gs->cnt[32], 1); }
      PROF(lane == 0 && mw == 0, 24);
    }
    const unsigned key = lds32(sb + OFF_MISC + 16);
    const int sel = 0xFFFF - (int)(key & 0xFFFF) - tm * 128;
    if (mw == 0 && sel >= 0 && sel < 128) {
      if (elect()) wait_counter(gs->cnt[32], MOD_CTAS);
      __syncwarp();
      const unsigned k16 = key >> 16;
      const float rs = bf_round(sigmoidf_(__uint_as_float(((k16 & 0x8000u) ? (k16 & 0x7FFFu) : (~k16 & 0xFFFFu)) << 16)));
      float4 v = make_float4(0.f, 0.f, 0.f, 0.f);
#pragma unroll 4
      for (int i = 0; i < 8; i++) {
        const float4 u = ld_relaxed_f4(gs->y[i] + tn * 128 + lane * 4);
        v.x += u.x; v.y += u.y; v.z += u.z; v.w += u.w;
      }
      mbar_wait(sb + BAR_X, 0);
      uint2* xp = (uint2*)(smem + OFF_PK + (lane >> 4) * 16384 + sel * 128 + ((((lane >> 1) & 7) ^ (sel & 7)) << 4) + (lane & 1) * 8);
      const uint2 xv = *xp;
      *xp = make_uint2(pack2(bf_lo(xv.x) + bf_round(bf_round(v.x) * rs), bf_hi(xv.x) + bf_round(bf_round(v.y) * rs)),
                       pack2(bf_lo(xv.y) + bf_round(bf_round(v.z) * rs), bf_hi(xv.y) + bf_round(bf_round(v.w) * rs)));
      __syncwarp();
      mbar_arrive_warp(sb + BAR_Y);
    }
  } else {
    asm volatile("setmaxnreg.inc.sync.aligned.u32 224;");
    const int w = warp & 3, wt = tid & 127;
    const int nb_self = NB_WG0 + wg;
    const uint32_t da0 = mkdesc(sb + OFF_RING, 16), db0 = mkdesc(sb + OFF_RING + A_BYTES, 8192);

    if (wg == 1) {
      float s[8] = {0.f, 0.f, 0.f, 0.f, 0.f, 0.f, 0.f, 0.f};
      const uint32_t zero = lds32(sb + OFF_ONES) & 1;
      uint32_t mask = 0xffff0000u;
#pragma unroll 1
      for (int i = 0; i < 4; i++) {
        const uint32_t u = RT_ORD >> i * 4 & 3;
        mbar_wait(sb + BAR_RT + i * 8, 0);
        const uint4 wr = lds128(sb + OFF_KVB + u * 512 + lane * 16), gw = lds128(sb + OFF_KVB + 2048 + u * 512 + lane * 16);
        uint4 xv[4];
#pragma unroll
        for (int r = 0; r < 4; r++) xv[r] = lds128(sb + OFF_PK + i * 8192 + (w * 4 + r) * 512 + lane * 16);
        const float wf[16] = {bf_lo(wr.x), bf_hi(wr.x), bf_lo(wr.y), bf_hi(wr.y), bf_lo(wr.z), bf_hi(wr.z), bf_lo(wr.w), bf_hi(wr.w),
                              bf_lo(gw.x), bf_hi(gw.x), bf_lo(gw.y), bf_hi(gw.y), bf_lo(gw.z), bf_hi(gw.z), bf_lo(gw.w), bf_hi(gw.w)};
#pragma unroll
        for (int r = 0; r < 4; r++) {
          const uint4 xq = xv[r];
          const float xf[8] = {bf_lo(xq.x), __uint_as_float(xq.x & mask), bf_lo(xq.y), bf_hi(xq.y), bf_lo(xq.z), bf_hi(xq.z), bf_lo(xq.w), bf_hi(xq.w)};
#pragma unroll
          for (int j = 0; j < 8; j++) { s[2 * r] = fmaf(xf[j ^ 1], wf[j ^ 1], s[2 * r]); s[2 * r + 1] = fmaf(xf[j ^ 1], wf[8 + (j ^ 1)], s[2 * r + 1]); }
          mask = ((__float_as_uint(s[2 * r]) | __float_as_uint(s[2 * r + 1])) & zero) | 0xffff0000u;
        }
      }
      mbar_arrive_warp(sb + BAR_RTD);
      float v = butterfly8(s, lane, 1);
      PROF_C(wt == 0 && v != 12345.f, 19);
      v += __shfl_xor_sync(~0u, v, 8);
      v = bf_round(v + __shfl_xor_sync(~0u, v, 16));
      const unsigned rb = __float_as_uint(v) >> 16, row = w * 4 + ((lane & 7) >> 1);
      unsigned key = (lane & 1) ? 0u : ((((rb & 0x8000u) ? (~rb & 0xFFFFu) : (rb | 0x8000u)) << 16) | ((15 - row) << 12));
      key = __reduce_max_sync(~0u, key);
      if (lane == 0) sts32(sb + OFF_MISC + w * 4, key);
      if (lane < 8 && (lane & 1)) sts32(sb + OFF_G + row * 4, __float_as_uint(bf_round(sigmoidf_(v))));
      nb_arrive(NB_KEY, 160);
      nb_sync(NB_ORDER_AB, 256);
    }

    uint32_t pq[2][4][4];
    float4* const kvacc = &gs->kv[wg][tn][0][wt];
    {
      float acc[2][96];
      PROF_C(wt == 0, 1 + wg * 8);
#pragma unroll 1
      for (int g = 0; g < 14; g++) {
        const uint32_t s = g & 3;
        const uint32_t da = da0 + s * (STAGE_BYTES >> 4), db = db0 + s * (STAGE_BYTES >> 4);
        mbar_wait(sb + BAR_FULL + s * 8, (g >> 2) & 1);
        PROF_C(wt == 0, 64 + wg * 16 + g);
#pragma unroll
        for (int m = 0; m < 2; m++) {
          wg_fence();
#pragma unroll
          for (int kk = 0; kk < 4; kk++) mma_qkv(acc[m], da + (m * 512 + kk * 2), db + kk * 128, kk ? 1 : g);
          wg_commit();
          if (m == 0) {
            wg_wait<1>();
            if (g) mbar_arrive_warp(sb + BAR_EMPTY + ((g + 3) & 3) * 8);
          }
        }
      }
      auto half_step = [&](int m, int g) {
        wg_fence();
#pragma unroll
        for (int kk = 0; kk < 4; kk++)
          mma_qkv(acc[m], da0 + ((g & 3) * (STAGE_BYTES >> 4) + m * 512 + kk * 2), db0 + ((g & 3) * (STAGE_BYTES >> 4) + kk * 128), 1);
        wg_commit();
      };
#pragma unroll
      for (int g = 14; g < 16; g++) {
        mbar_wait(sb + BAR_FULL + (g & 3) * 8, 1);
        PROF_C(wt == 0, 64 + wg * 16 + g);
        half_step(0, g);
        if (g == 14) { wg_wait<1>(); mbar_arrive_warp(sb + BAR_EMPTY + ((g + 3) & 3) * 8); }
      }
      half_step(1, 14);
      half_step(1, 15);
      if (wg == 0) nb_arrive(NB_ORDER_AB, 256);
      mbar_wait(sb + BAR_IDX, 0);
      if (wg == 1) nb_sync(NB_STG, 256);
      wg_wait<2>();
      PROF_C(wt == 0, 3 + wg * 8);

      const uint32_t st_row = (uint32_t)(w * 16 + (lane & 15)) * 128;
      float c[36];
      const uint32_t dk = mkdesc(sb + OFF_PK, 16), dv = mkdesc(sb + OFF_V, OFF_ONES - OFF_V);
      uint32_t l2k[8 + PA];
#pragma unroll
      for (int u = 0; u < PA; u++) l2k[u] = 0x3FB8AA3Bu;
#pragma unroll
      for (int u = 0; u < 8; u++) {
        const int m = u >> 2, j = u & 3;
        const uint32_t a = sb + m * 8192 + st_row + ((((lane >> 4) + 2 * j) ^ (lane & 7)) << 4);
        const float* k = &acc[m][32 + 8 * j];
        const float l = __uint_as_float(l2k[u]);
        if (u == M1) {
          wg_wait<1>();
          mbar_arrive_warp(sb + BAR_EMPTY + 2 * 8);
        }
        if (u == MM) {
          wg_wait<0>();
          mbar_arrive_warp(sb + BAR_EMPTY + 3 * 8);
        }
        const float* v = &acc[m][64 + 8 * j];
        stsm4(a + OFF_V, pack2(v[0], v[1]), pack2(v[2], v[3]), pack2(v[4], v[5]), pack2(v[6], v[7]));
        const uint32_t r0 = phi2(k[0], k[1], l), r1 = phi2(k[2], k[3], l), r2 = phi2(k[4], k[5], l), r3 = phi2(k[6], k[7], l);
        stsm4(a + OFF_PK, r0, r1, r2, r3);
        if (u + PA < 8) l2k[u + PA] = lds32(sb + OFF_MISC + 20);
      }
      fence_async_smem();
      nb_sync(nb_self, 128);
      PROF_C(wt == 0, 8 + wg * 8);
      wg_fence();
#pragma unroll
      for (int kk = 0; kk < 8; kk++) mma_ktv(c, dk + kk * 128, dv + (kk * 128 - (kk << 23)), kk ? 1 : 0);
      wg_commit();
      if (wg == 1) nb_arrive(NB_ORDER_BO, 256);
      auto reduce = [&](float4* dst, int gap) {
        wg_wait<0>();
        PROF_C(wt == 0, 4 + wg * 8);
        float u[18];
#pragma unroll
        for (int i = 0; i < 16; i++) u[i] = w >= 2 ? c[16 + i] : c[i];
        u[16] = __shfl_down_sync(~0u, u[15], 1);
        u[17] = lane & 2 ? c[34] : c[32];
#pragma unroll
        for (int i = 0; i < 5; i++) {
          if (gap && i) __nanosleep(gap);
          red_add4(dst + i * 128, u[3 * i], u[3 * i + 1], u[3 * i + 2], i < 3 && !(lane & 1) ? u[i == 0 ? 15 : i == 1 ? 17 : 16] : 1.f);
        }
      };
      const uint32_t zero = lds32(sb + OFF_ONES) & 1;
      if (wg) reduce(kvacc, 0);
      const float l2e = __uint_as_float(lds32(sb + OFF_MISC + 20));
      uint32_t dep = 0;
#pragma unroll
      for (int u = 0; u < 8; u++) {
#pragma unroll
        for (int i = 0; i < 4; i++) dep |= pq[u >> 2][u & 3][i] = phi2(acc[u >> 2][8 * (u & 3) + 2 * i], acc[u >> 2][8 * (u & 3) + 2 * i + 1], l2e);
      }
      float4* const kvp = kvacc + (dep & zero);
      if (!wg) reduce(kvp, RED_SLEEP);
      PROF_C(wt == 0 && kvp == kvacc, 34 + wg * 2);
      for (int tries = wg ? 0 : 9;; tries++) {
        if (tries > RETRY)
          while (ld_relaxed((const unsigned*)&(kvp - lane)[NV * 128 - 128 + 31].w) != 0x41800000u) __nanosleep(wg ? KV_SLEEP : KV_SLEEP_A);
        float4 kv[NV];
#pragma unroll
        for (int i = 0; i < NV; i++) kv[i] = ld_relaxed_f4(kvp + i * 128);
        const uint32_t kb = sb + OFF_KVB + (w >> 1) * 2560 + (w & 1) * 256;
        const uint32_t ka = kb + (lane >> 4) * 512 + (lane & 15) * 16;
        stsm4(ka, pack2(kv[0].x, kv[0].y), pack2(kv[0].z, kv[1].x), pack2(kv[1].y, kv[1].z), pack2(kv[2].x, kv[2].y));
        const uint32_t zz = pack2(kv[1].w, kv[1].w);
        if (!(lane & 1)) sts128(kb + 2048 + (lane & 2) * 64 + (lane >> 2) * 16, zz, zz, zz, zz);
        const float u15 = __shfl_up_sync(~0u, kv[2].w, 1);
        stsm4(ka + 1024, pack2(kv[2].z, kv[3].x), pack2(kv[3].y, kv[3].z), pack2(kv[4].x, kv[4].y), pack2(kv[4].z, lane & 1 ? u15 : kv[0].w));
        const bool ok = !(lane & 1) || kv[0].w + kv[1].w + kv[2].w + kv[3].w + kv[4].w == 80.f;
        if (__all_sync(~0u, ok)) { PROF_V(wg && lane == 0, 40 + w, tries * 100 + 2); break; }
      }
    }
    {
      PROF_C(wt == 0, 5 + wg * 8);
      fence_async_smem();
      nb_sync(nb_self, 128);
      float o[2][2][20];
      const uint32_t dz = mkdesc(sb + OFF_KVB, 128);
      wg_fence();
#pragma unroll
      for (int m = 0; m < 2; m++) {
#pragma unroll
        for (int h = 0; h < 2; h++)
#pragma unroll
          for (int kk = 0; kk < 2; kk++) mma_qkvz(o[m][h], pq[m][2 * h + kk], dz + (h * 160 + kk * 16), kk);
        wg_commit();
      }
      const uint32_t tmask = (lane & 3) == (lane >> 3), tbit = lds32(sb + OFF_MISC + 24) & tmask;
      float gr[2][2], sc[4];
#pragma unroll
      for (int i = 0; i < 4; i++) gr[i >> 1][i & 1] = __uint_as_float(lds32(sb + OFF_G + ((i >> 1) * 64 + (i & 1) * 8 + w * 16 + (lane >> 2)) * 4));
      if (wg == 1) {
        mbar_arrive_warp(sb + BAR_OST);
        mbar_wait(sb + BAR_OA, 0);
      }
      const uint32_t os = sb + (wg ? OFF_MOD : OFF_PK) + w * 2048;
      uint8_t* const og = (uint8_t*)gs->o[tm][wg * 8 + tn] + w * 2048;
#pragma unroll
      for (int m = 0; m < 2; m++) {
        if (m == 0) wg_wait<1>();
        if (m == 0) PROF_C(wt == 0, 6 + wg * 8);
#pragma unroll
        for (int h = 0; h < 2; h++) {
          const float* oo = o[m][h];
          uint32_t pin = 0;
          if (!m && h) {
            wg_wait<0>();
#pragma unroll
            for (int i = 0; i < 4; i++) pin |= __float_as_uint(sc[i] = gr[1][i & 1] * rcp(o[1][i >> 1][16 + (i & 1) * 2] + 1e-6f));
            pin &= __float_as_uint(gr[0][0]) & 16;
          }
          const float s0 = m ? sc[2 * h] : gr[m][0] * rcp(oo[16] + 1e-6f), s1 = m ? sc[2 * h + 1] : gr[m][1] * rcp(oo[18] + 1e-6f);
#pragma unroll
          for (int j = 0; j < 2; j++)
            stsm4(os + m * 8192 + (lane & 15) * 128 + ((((lane >> 4) + 4 * h + 2 * j) ^ (lane & 7)) << 4) + (j ? pin : 0),
                  (pack2(oo[8 * j] * s0, oo[8 * j + 1] * s0) & ~tmask) | tbit, (pack2(oo[8 * j + 2] * s1, oo[8 * j + 3] * s1) & ~tmask) | tbit,
                  pack2(oo[8 * j + 4] * s0, oo[8 * j + 5] * s0), pack2(oo[8 * j + 6] * s1, oo[8 * j + 7] * s1));
        }
        fence_async_smem();
        __syncwarp();
        if (elect()) bulk_store(og + m * 8192, os + m * 8192, 2048);
      }
      if (elect()) {
        bulk_commit();
        if (wg) mbar_arrive(sb + BAR_OWN);
        PROF(wt == 0, 7 + wg * 8);
        if (!wg) red_add(gs->cnt[tm], 1u << tn * 4);
        asm volatile("cp.async.bulk.wait_group.read 0;" ::: "memory");
        PROF(wt == 0, 17 + wg);
        PROF(wt == 96, 38 + wg);
      }
    }

    __syncwarp();
    const uint32_t par = lds32(sb + OFF_MISC + 24), cw = lane * 32 + (lane & 4) * 4 + (lane >> 3) * 4;
    auto check_tile = [&](int g, uint32_t s) {
      const uint32_t a = sb + OFF_RING + s * O_BYTES + w * 2048, fix = sb + BAR_FIX + warp * 8;
      for (;;) {
        const uint32_t u0 = lds32(a + cw), u1 = lds32(a + cw + 1024), u2 = lds32(a + cw + 8192), u3 = lds32(a + cw + 9216);
        if (__all_sync(~0u, !(mism(mism(u0, u1, par), mism(u2, u3, par), 0) & 1))) break;
        PROF_V(lane == 0, 44 + g, 102);
        const int slab = g < OWN ? g : g < PEER ? g - 1 : g == PEER ? 8 + (tn ^ 1) : g - 10 < (tn & 6) ? g - 2 : g;
        const uint4* src = gs->o[tm][slab] + w * 128;
        const uint32_t ph = !mbar_test(fix, 1);
        fence_async_smem();
        __syncwarp();
        if (elect()) { mbar_expect_tx(fix, 4096); bulk_load(a, src, 2048, fix); bulk_load(a + 8192, src + 512, 2048, fix); }
        mbar_wait(fix, ph);
      }
    };
    if (wg == 1) {
#pragma unroll 1
      for (int g = 10; g < 16; g++) {
        const uint32_t s = g == 15 ? 0 : g - 10;
        mbar_wait(sb + BAR_LAND + (g - 10) * 8, 0);
        PROF_C(wt == 0, 214 + g);
        check_tile(g, s);
        if (w) nb_arrive(NB_CHK + (g & 1), 128);
        else { nb_sync(NB_CHK + (g & 1), 128); mbar_arrive_warp(sb + BAR_FULL + s * 8); }
        if (g & 1) nb_sync(nb_self, 128);
      }
    } else {
      nb_arrive(NB_STG, 256);
      float acc[2][64];
      mbar_wait(sb + BAR_W31, 0);
#pragma unroll 1
      for (int g = 0; g < PC; g++) { mbar_wait(sb + BAR_EMPTY + g * 8, 1); mbar_wait(sb + BAR_FULL + g * 8, 0); check_tile(g, g); }
      const uint32_t chk = __shfl_sync(~0u, lds32(sb + OFF_MISC + 28), 0);
      nb_sync(NB_ORDER_BO, 256);
      PROF_C(wt == 0, 26);
      uint32_t xr[2][8][4], q[2][2];
      const uint32_t ta = sb + OFF_PK + (uint32_t)(w * 16 + (lane & 15)) * 128;
#pragma unroll 1
      for (int g = 0; g < 13 - TL; g++) {
        const uint32_t r = g * 52 >> 8, s = g - r * 5;
        const uint32_t da = da0 + (g == OWN ? 5 : s) * (O_BYTES >> 4), db = db0 + s * (O_BYTES >> 4);
        if (g == OWN) {
          wg_wait<0>();
          mbar_arrive_warp(sb + BAR_EMPTY + (OWN + 4) % 5 * 8);
          mbar_wait(sb + BAR_OWN, 0);
        }
        mbar_wait(sb + BAR_FULL + s * 8, r & 1);
        if (chk >> g & 1) check_tile(g, s);
        PROF_C(wt == 0, 96 + g);
        wg_fence();
#pragma unroll
        for (int kk = 0; kk < 4; kk++)
#pragma unroll
          for (int m = 0; m < 2; m++) mma_out(acc[m], da + (m * 512 + kk * 2), db + kk * 128, kk ? 1 : g);
        wg_commit();
        wg_wait<1>();
        if (~(1 | 1 << OWN) >> g & 1) mbar_arrive_warp(sb + BAR_EMPTY + (s ? s - 1 : 4) * 8);
      }
      auto fetch_x = [&](int u) {
        if (u == (XG & 7)) {
          mbar_wait(sb + BAR_X, 0);
          if (((0xFFFF - (lds32(sb + OFF_MISC + 16) & 0xFFFF)) >> 7) == tm) mbar_wait(sb + BAR_Y, 0);
        }
#pragma unroll
        for (int v = 0; v < 4; v++) {
          if ((XG >> v * 4 & 7) != u) continue;
          const int m = v >> 1;
          const float g1 = 1.f - __uint_as_float(lds32(sb + OFF_G + (m * 64 + w * 16 + (v & 1) * 8 + (lane >> 2)) * 4));
          q[m][v & 1] = pack2(g1, g1);
#pragma unroll
          for (int j = 0; j < 4; j++) ldsm4(ta + (v & 1) * 16384 + m * 8192 + ((((lane >> 4) + 2 * j) ^ (lane & 7)) << 4), xr[m][(v & 1) * 4 + j]);
        }
      };
#pragma unroll
      for (int u = 0; u < 4; u++) {
        const int g = 13 - TL + u;
        fetch_x(u);
        if (u == 3) break;
        mbar_wait(sb + BAR_FULL + g % 5 * 8, g / 5 & 1);
        PROF_C(wt == 0, 96 + g);
        wg_fence();
#pragma unroll
        for (int kk = 0; kk < 4; kk++)
#pragma unroll
          for (int mm = 0; mm < 2; mm++)
            mma_out(acc[mm], da0 + (g % 5 * (O_BYTES >> 4) + mm * 512 + kk * 2), db0 + (g % 5 * (O_BYTES >> 4) + kk * 128), 1);
        wg_commit();
        wg_wait<1>();
        if (g <= 11) mbar_arrive_warp(sb + BAR_EMPTY + (g + 4) % 5 * 8);
      }
      auto half_step = [&](int m, int g) {
        if (m == 0) { mbar_wait(sb + BAR_FULL + g % 5 * 8, g / 5 & 1); PROF_C(wt == 0, 96 + g); wg_fence(); }
#pragma unroll
        for (int kk = 0; kk < 4; kk++)
          mma_out(acc[m], da0 + (g % 5 * (O_BYTES >> 4) + m * 512 + kk * 2), db0 + (g % 5 * (O_BYTES >> 4) + kk * 128), 1);
      };
      auto stage = [&](int m, int j0, int j1) {
#pragma unroll
        for (int j = j0; j < j1; j++) {
          const float* v = &acc[m][8 * j];
          stsm4(ta + (j >> 2) * 16384 + m * 8192 + ((((lane >> 4) + 2 * (j & 3)) ^ (lane & 7)) << 4),
                fma_bf2(xr[m][j][0], q[m][0], pack2(v[0], v[1])), fma_bf2(xr[m][j][1], q[m][1], pack2(v[2], v[3])),
                fma_bf2(xr[m][j][2], q[m][0], pack2(v[4], v[5])), fma_bf2(xr[m][j][3], q[m][1], pack2(v[6], v[7])));
        }
      };
      auto leave_tma = [&](int m, int h) {
        fence_async_smem();
        __syncwarp();
        if (elect()) tma2d_store(&p.out, sb + OFF_PK + h * 16384 + m * 8192 + w * 2048, tn * 128 + h * 64, tm * 128 + m * 64 + w * 16);
      };
      auto leave = [&](int m, int h) {
        __syncwarp();
        const uint32_t r = lane >> 3;
        uint4 v[4];
#pragma unroll
        for (int i = 0; i < 4; i++) v[i] = lds128(sb + OFF_PK + h * 16384 + m * 8192 + w * 2048 + (r + 4 * i) * 128 + (((lane ^ (r + 4 * i)) & 7) << 4));
        char* const dst = (char*)pout + (size_t)(tm * 128 + m * 64 + w * 16 + r) * (D_ * 2) + tn * 256 + h * 128 + (lane & 7) * 16;
#pragma unroll
        for (int i = 0; i < 4; i++) asm volatile("st.global.v4.u32 [%0], {%1, %2, %3, %4};" ::"l"(dst + i * 4 * D_ * 2), "r"(v[i].x), "r"(v[i].y), "r"(v[i].z), "r"(v[i].w) : "memory");
      };
#pragma unroll
      for (int g = 16 - TL; g < 16; g++) half_step(0, g);
      wg_commit();
      fetch_x(4);
#pragma unroll
      for (int g = 16 - TL; g < 16; g++) half_step(1, g);
      wg_commit();
      mbar_arrive_warp(sb + BAR_DONE);
      wg_wait<1>();
      PROF(wt == 0, 35);
      stage(0, 0, 4);
      leave_tma(0, 0);
      stage(0, 4, 8);
      leave_tma(0, 1);
      if (elect()) bulk_commit();
      PROF(wt == 0, 33);
      wg_wait<0>();
      PROF(wt == 0, 31);
#pragma unroll
      for (int h = 0; h < 2; h++) { stage(1, 4 * h, 4 * h + 4); leave(1, h); }
      if (elect()) asm volatile("cp.async.bulk.wait_group.read 0;" ::: "memory");
      PROF(wt == 0, 32);
    }
  }
}

typedef CUresult (*EncodeFn)(CUtensorMap*, CUtensorMapDataType, cuuint32_t, void*, const cuuint64_t*, const cuuint64_t*, const cuuint32_t*,
                             const cuuint32_t*, CUtensorMapInterleave, CUtensorMapSwizzle, CUtensorMapL2promotion, CUtensorMapFloatOOBfill);

void encode(EncodeFn fn, CUtensorMap* m, const void* ptr, int rank, const cuuint64_t* dims, const cuuint64_t* strides, const cuuint32_t* box,
            CUtensorMapSwizzle sw, CUtensorMapDataType dt = CU_TENSOR_MAP_DATA_TYPE_BFLOAT16) {
  const cuuint32_t es[3] = {1, 1, 1};
  fn(m, dt, rank, const_cast<void*>(ptr), dims, strides, box, es, CU_TENSOR_MAP_INTERLEAVE_NONE, sw,
     CU_TENSOR_MAP_L2_PROMOTION_L2_128B, CU_TENSOR_MAP_FLOAT_OOB_FILL_NONE);
}

}

extern "C" void kernel_launch(void* const* d_in, const int* in_sizes, int n_in, void* d_out, int out_size) {
  (void)in_sizes; (void)n_in; (void)out_size;
  EncodeFn fn = nullptr;
  cudaDriverEntryPointQueryResult qr;
  cudaGetDriverEntryPoint("cuTensorMapEncodeTiled", (void**)&fn, cudaEnableDefault, &qr);

  Params p;
  {
    const cuuint64_t dims[2] = {D_, S_}, str[1] = {D_ * 2};
    const cuuint32_t box[2] = {64, 128}, box_st[2] = {64, 16}, box_r[2] = {256, 16};
    encode(fn, &p.xr, d_in[0], 2, dims, str, box_r, CU_TENSOR_MAP_SWIZZLE_NONE);
    encode(fn, &p.x, d_in[0], 2, dims, str, box, CU_TENSOR_MAP_SWIZZLE_128B);
    encode(fn, &p.out, d_out, 2, dims, str, box_st, CU_TENSOR_MAP_SWIZZLE_128B);
  }
  {
    const cuuint64_t dims[3] = {D_, D_, 3}, str[2] = {3 * D_ * 2, D_ * 2};
    const cuuint32_t box[3] = {64, 64, 3};
    encode(fn, &p.w, d_in[1], 3, dims, str, box, CU_TENSOR_MAP_SWIZZLE_128B);
  }
  {
    const cuuint64_t dims[3] = {64, D_, D_ / 64}, str[2] = {D_ * 2, 128};
    const cuuint32_t box[3] = {64, 64, 2};
    encode(fn, &p.wo, d_in[2], 3, dims, str, box, CU_TENSOR_MAP_SWIZZLE_128B);
  }
  {
    const cuuint64_t dims[3] = {F_, D_ / 4, 4}, str[2] = {F_ * 8, F_ * 2};
    const cuuint32_t box[3] = {32, 16, 4};
    encode(fn, &p.gate, d_in[5], 3, dims, str, box, CU_TENSOR_MAP_SWIZZLE_NONE);
    encode(fn, &p.up, d_in[6], 3, dims, str, box, CU_TENSOR_MAP_SWIZZLE_NONE);
  }
  {
    const cuuint64_t dims[3] = {D_ / 4, F_, 2}, str[2] = {D_ * 2, D_};
    const cuuint32_t box[3] = {256, 4, 2};
    encode(fn, &p.down, d_in[7], 3, dims, str, box, CU_TENSOR_MAP_SWIZZLE_NONE, CU_TENSOR_MAP_DATA_TYPE_UINT32);
  }
  void* gs = nullptr;
  cudaGetSymbolAddress(&gs, g_scratch);
  typedef const __nv_bfloat16* bp;
  int dev = 0, sms = 0;
  cudaGetDevice(&dev);
  cudaDeviceGetAttribute(&sms, cudaDevAttrMultiProcessorCount, dev);
  const bool by_sm = BYSM && sms == NGRID;
  const auto kernel = by_sm ? fused_kernel<true> : fused_kernel<false>;
  cudaFuncSetAttribute(kernel, cudaFuncAttributeMaxDynamicSharedMemorySize, SMEM_BYTES);
  kernel<<<by_sm ? NGRID : NCTA, NTHREADS, SMEM_BYTES, cudaStreamPerThread>>>((bp)d_in[0], (Scratch*)gs, d_out, (bp)d_in[4], (bp)d_in[8], (bp)d_in[5], p, (bp)d_in[6]);
}
```
